```python
import torch

def _softmax(x, axis=-1):
    return torch.softmax(x, dim=axis)

def _gelu(x):
    return torch.nn.functional.gelu(x, approximate='tanh')

def _silu(x):
    return torch.nn.functional.silu(x)

def _sigmoid(x):
    return torch.sigmoid(x)

def _layernorm(x, axis=-1, eps=1e-05):
    m = x.mean(dim=axis, keepdim=True)
    v = x.var(dim=axis, keepdim=True, unbiased=False)
    return (x - m) / torch.sqrt(v + eps)

def _scatter_add(tgt, idx, src, axis=0):
    return tgt.clone().index_add_(axis, idx, src)

def _segment_sum(src, seg, n):
    out = torch.zeros((n,) + src.shape[1:], dtype=src.dtype)
    return out.index_add_(0, seg, src)

def _pad(x, pw):
    flat = tuple((v for pair in reversed(pw) for v in pair))
    return torch.nn.functional.pad(x, flat)
kernel_name = 'sequential_preLN__memory_aug_recurrent_mem_tr__dense_activation_gelu__prompt'

def setup_inputs():

    _w = lambda a: (lambda t: t.to(torch.bfloat16) if t.is_floating_point() else t)(torch.as_tensor(a))

    def _A_setup():
        B, S, Dm = (1, 2048, 576)
        H, Dh = (32, 128)
        M, seg = (8, 32)
        seg = min(seg, S)
        S = S // seg * seg
        return {'x': _w((lambda *s: torch.randn(*s, dtype=torch.bfloat16) * 0.05)(B, S, Dm)), 'mem0': _w((lambda *s: torch.randn(*s, dtype=torch.bfloat16) * 0.2)(B, M, Dm)), 'Wq': _w((lambda *s: torch.randn(*s, dtype=torch.bfloat16) * 1.6)(Dm, H, Dh) * Dm ** (-0.5)), 'Wk': _w((lambda *s: torch.randn(*s, dtype=torch.bfloat16) * 1.6)(Dm, H, Dh) * Dm ** (-0.5)), 'Wv': _w((lambda *s: torch.randn(*s, dtype=torch.bfloat16) * 0.2)(Dm, H, Dh) * Dm ** (-0.5)), 'Wo': _w((lambda *s: torch.randn(*s, dtype=torch.bfloat16) * 0.2)(H, Dh, Dm) * (H * Dh) ** (-0.5)), 'seg_len': seg}
    _A_in = _A_setup()

    def _B_setup():
        B, S, D, F = (1, 2048, 576, 4608)
        return {'x': _w((lambda *s: torch.randn(*s, dtype=torch.bfloat16) * 0.05)(B, S, D)), 'w1': _w((lambda *s: torch.randn(*s, dtype=torch.bfloat16) * 0.4)(D, F) * D ** (-0.5)), 'b1': _w((lambda *s: torch.randn(*s, dtype=torch.bfloat16) * 12.8)(F) * 0.01), 'w2': _w((lambda *s: torch.randn(*s, dtype=torch.bfloat16) * 0.2)(F, D) * F ** (-0.5)), 'b2': _w((lambda *s: torch.randn(*s, dtype=torch.bfloat16) * 3.2)(D) * 0.01)}
    _B_in = _B_setup()
    return {'A_x': _A_in['x'], 'A_mem0': _A_in['mem0'], 'A_Wq': _A_in['Wq'], 'A_Wk': _A_in['Wk'], 'A_Wv': _A_in['Wv'], 'A_Wo': _A_in['Wo'], 'A_seg_len': _A_in['seg_len'], 'B_x': _B_in['x'], 'B_w1': _B_in['w1'], 'B_b1': _B_in['b1'], 'B_w2': _B_in['w2'], 'B_b2': _B_in['b2']}

def reference(A_x, A_mem0, A_Wq, A_Wk, A_Wv, A_Wo, A_seg_len, B_x, B_w1, B_b1, B_w2, B_b2):

    def _A_ref(x, mem0, Wq, Wk, Wv, Wo, seg_len):
        B, S, Dm = x.shape
        H, Dh = (Wq.shape[1], Wq.shape[2])
        M = mem0.shape[1]
        scale = Dh ** (-0.5)
        n_seg = S // seg_len
        L = M + seg_len
        idx = torch.arange(L)
        mask = (idx[:, None] < M) | (idx[:, None] >= idx[None, :])
        mem = mem0
        outs = []
        for s in range(n_seg):
            xs = x[:, s * seg_len:(s + 1) * seg_len, :].clone()
            h = torch.concatenate([mem, xs], axis=1)
            q = torch.einsum('btd,dhe->bhte', h, Wq)
            k = torch.einsum('btd,dhe->bhte', h, Wk)
            v = torch.einsum('btd,dhe->bhte', h, Wv)
            scores = torch.einsum('bhqe,bhke->bhqk', q, k) * scale
            scores = torch.where(mask[None, None], scores, -1000000000.0)
            p = _softmax(scores, axis=-1)
            o = torch.einsum('bhqk,bhke->bhqe', p, v)
            o = torch.einsum('bhte,hed->btd', o, Wo)
            mem = o[:, :M, :].clone()
            outs.append(o[:, M:, :])
        return torch.concatenate(outs, axis=1)

    def _B_ref(x, w1, b1, w2, b2):
        h = torch.einsum('bsd,df->bsf', x, w1) + b1
        h = _gelu(h)
        return torch.einsum('bsf,fd->bsd', h, w2) + b2
    x = A_x
    h = x + _A_ref(_layernorm(x, axis=-1), A_mem0, A_Wq, A_Wk, A_Wv, A_Wo, A_seg_len)
    h2 = h + _B_ref(_layernorm(h, axis=-1), B_w1, B_b1, B_w2, B_b2)
    return h2
```

```cpp
#include <cuda_runtime.h>
#include <cuda_bf16.h>
#include <cuda.h>
#include <stdint.h>

namespace {

constexpr int SEQ = 2048, DM = 576, NH = 32, DH = 128, NSEG = 64, FF = 4608, HD = 4096;
constexpr int XN_SEG_BYTES = 32 * DM * 2;
constexpr int NOWN = 72;
constexpr int SPIN_LIMIT = 1 << 20;

__device__ __align__(1024) uint8_t g_xn[NSEG * XN_SEG_BYTES];
__device__ __align__(1024) uint8_t g_ox[SEQ * HD * 2];
__device__ __align__(1024) uint8_t g_xch[(NOWN + 3) * 65536];
__device__ uint32_t g_tab[128];
__device__ __align__(1024) uint8_t g_hb[SEQ * DM * 2];
__device__ __align__(1024) uint8_t g_ff[SEQ * FF * 2];
__device__ __align__(1024) float4 g_part[2 * 16 * 3 * 24 * 256];
__device__ __align__(128) float2 g_stat[16 * 3 * 128];
__device__ __align__(128) float2 g_cb[FF];
constexpr int FL_OX = 0, FL_H = 1, FL_FF = 2, FL_CW = 4, FL_C1 = 5, FL_C2 = 6, FL_DONE = 8  , FL_INIT = 256, FL_CINIT = 257;
__device__ __align__(128) uint32_t g_flag[17 * 16];
#define TLOG_END()

__device__ __forceinline__ uint32_t smem_u32(const void* p) { return (uint32_t)__cvta_generic_to_shared(p); }
__device__ __forceinline__ uint32_t mapa(uint32_t a, uint32_t r) {
    uint32_t o; asm("mapa.shared::cluster.u32 %0,%1,%2;" : "=r"(o) : "r"(a), "r"(r)); return o;
}
__device__ __forceinline__ void mbar_init(uint32_t bar, uint32_t cnt) {
    asm volatile("mbarrier.init.shared::cta.b64 [%0],%1;" ::"r"(bar), "r"(cnt) : "memory");
}
__device__ __forceinline__ void mbar_expect_tx(uint32_t bar, uint32_t bytes) {
    asm volatile("mbarrier.arrive.expect_tx.shared::cta.b64 _,[%0],%1;" ::"r"(bar), "r"(bytes) : "memory");
}
__device__ __forceinline__ void mbar_arrive(uint32_t bar) {
    asm volatile("mbarrier.arrive.shared::cta.b64 _,[%0];" ::"r"(bar) : "memory");
}
__device__ __forceinline__ bool mbar_try(uint32_t bar, uint32_t ph) {
    uint32_t ok;
    asm volatile("{.reg .pred p; mbarrier.try_wait.parity.shared::cta.b64 p,[%1],%2; selp.u32 %0,1,0,p;}"
                 : "=r"(ok) : "r"(bar), "r"(ph) : "memory");
    return ok;
}
__device__ __forceinline__ bool mbar_try_cluster(uint32_t bar, uint32_t ph) {
    uint32_t ok;
    asm volatile("{.reg .pred p; mbarrier.try_wait.parity.acquire.cluster.shared::cta.b64 p,[%1],%2; selp.u32 %0,1,0,p;}"
                 : "=r"(ok) : "r"(bar), "r"(ph) : "memory");
    return ok;
}
__device__ __forceinline__ void mbar_wait(uint32_t bar, uint32_t ph, int& dead) {
    if (dead) return;
    int n = 0;
    while (!mbar_try(bar, ph)) { if (++n > SPIN_LIMIT) { dead = 1; break; } }
}
__device__ __forceinline__ void mbar_wait_cluster(uint32_t bar, uint32_t ph, int& dead) {
    if (dead) return;
    int n = 0;
    while (!mbar_try_cluster(bar, ph)) { if (++n > SPIN_LIMIT) { dead = 1; break; } }
}
__device__ __forceinline__ void bar_sync(int id, int n) { asm volatile("bar.sync %0,%1;" ::"r"(id), "r"(n) : "memory"); }
__device__ __forceinline__ void bar_arrive(int id, int n) { asm volatile("bar.arrive %0,%1;" ::"r"(id), "r"(n) : "memory"); }
__device__ __forceinline__ void cluster_sync() {
    asm volatile("barrier.cluster.arrive.release.aligned;\nbarrier.cluster.wait.acquire.aligned;" ::: "memory");
}
__device__ __forceinline__ void fence_async() { asm volatile("fence.proxy.async.shared::cta;" ::: "memory"); }

__device__ __forceinline__ void ldsm4(uint32_t (&r)[4], uint32_t a) {
    asm volatile("ldmatrix.sync.aligned.m8n8.x4.shared.b16 {%0,%1,%2,%3},[%4];"
                 : "=r"(r[0]), "=r"(r[1]), "=r"(r[2]), "=r"(r[3]) : "r"(a) : "memory");
}
__device__ __forceinline__ void ldsm4t(uint32_t (&r)[4], uint32_t a) {
    asm volatile("ldmatrix.sync.aligned.m8n8.x4.trans.shared.b16 {%0,%1,%2,%3},[%4];"
                 : "=r"(r[0]), "=r"(r[1]), "=r"(r[2]), "=r"(r[3]) : "r"(a) : "memory");
}
__device__ __forceinline__ void stsm4(uint32_t a, uint32_t r0, uint32_t r1, uint32_t r2, uint32_t r3) {
    asm volatile("stmatrix.sync.aligned.m8n8.x4.shared.b16 [%0],{%1,%2,%3,%4};" ::"r"(a), "r"(r0), "r"(r1), "r"(r2), "r"(r3) : "memory");
}
__device__ __forceinline__ void stsm4t(uint32_t a, uint32_t r0, uint32_t r1, uint32_t r2, uint32_t r3) {
    asm volatile("stmatrix.sync.aligned.m8n8.x4.trans.shared.b16 [%0],{%1,%2,%3,%4};" ::"r"(a), "r"(r0), "r"(r1), "r"(r2), "r"(r3) : "memory");
}
__device__ __forceinline__ void mma16(float (&d)[4], uint32_t a0, uint32_t a1, uint32_t a2, uint32_t a3, uint32_t b0, uint32_t b1) {
    asm volatile("mma.sync.aligned.m16n8k16.row.col.f32.bf16.bf16.f32 {%0,%1,%2,%3},{%4,%5,%6,%7},{%8,%9},{%0,%1,%2,%3};"
                 : "+f"(d[0]), "+f"(d[1]), "+f"(d[2]), "+f"(d[3]) : "r"(a0), "r"(a1), "r"(a2), "r"(a3), "r"(b0), "r"(b1));
}
__device__ __forceinline__ void mma8(float (&d)[4], uint32_t a0, uint32_t a1, uint32_t b0) {
    asm volatile("mma.sync.aligned.m16n8k8.row.col.f32.bf16.bf16.f32 {%0,%1,%2,%3},{%4,%5},{%6},{%0,%1,%2,%3};"
                 : "+f"(d[0]), "+f"(d[1]), "+f"(d[2]), "+f"(d[3]) : "r"(a0), "r"(a1), "r"(b0));
}
__device__ __forceinline__ uint32_t pack_bf16(float lo, float hi) {
    uint32_t r; asm("cvt.rn.bf16x2.f32 %0,%1,%2;" : "=r"(r) : "f"(hi), "f"(lo)); return r;
}
__device__ __forceinline__ float ex2(float x) { float r; asm("ex2.approx.ftz.f32 %0,%1;" : "=f"(r) : "f"(x)); return r; }
__device__ __forceinline__ void st_async32(uint32_t dst, uint32_t v, uint32_t bar) {
    asm volatile("st.async.shared::cluster.mbarrier::complete_tx::bytes.u32 [%0],%1,[%2];" ::"r"(dst), "r"(v), "r"(bar) : "memory");
}
__device__ __forceinline__ void bulk_g2s(uint32_t dst, const void* src, uint32_t bytes, uint32_t bar) {
    asm volatile("cp.async.bulk.shared::cluster.global.mbarrier::complete_tx::bytes [%0],[%1],%2,[%3];"
                 ::"r"(dst), "l"(src), "r"(bytes), "r"(bar) : "memory");
}
__device__ __forceinline__ void bulk_g2s_mc(uint32_t dst, const void* src, uint32_t bytes, uint32_t bar, uint16_t mask) {
    asm volatile("cp.async.bulk.shared::cluster.global.mbarrier::complete_tx::bytes.multicast::cluster [%0],[%1],%2,[%3],%4;"
                 ::"r"(dst), "l"(src), "r"(bytes), "r"(bar), "h"(mask) : "memory");
}
__device__ __forceinline__ void bulk_s2s(uint32_t dst, uint32_t src, uint32_t bytes, uint32_t bar) {
    asm volatile("cp.async.bulk.shared::cluster.shared::cta.mbarrier::complete_tx::bytes [%0],[%1],%2,[%3];"
                 ::"r"(dst), "r"(src), "r"(bytes), "r"(bar) : "memory");
}
__device__ __forceinline__ void cp_async16(uint32_t dst, const void* src) {
    asm volatile("cp.async.cg.shared.global [%0],[%1],16;" ::"r"(dst), "l"(src) : "memory");
}
__device__ __forceinline__ uint4 ld_relaxed4(const void* p) {
    uint4 v;
    asm volatile("ld.relaxed.gpu.global.v4.u32 {%0,%1,%2,%3},[%4];" : "=r"(v.x), "=r"(v.y), "=r"(v.z), "=r"(v.w) : "l"(p) : "memory");
    return v;
}
__device__ __forceinline__ void st_relaxed2(void* p, uint32_t a, uint32_t b) {
    asm volatile("st.relaxed.gpu.global.v2.u32 [%0],{%1,%2};" ::"l"(p), "r"(a), "r"(b) : "memory");
}
__device__ __forceinline__ void st_relaxed1(void* p, uint32_t a) {
    asm volatile("st.relaxed.gpu.global.u32 [%0],%1;" ::"l"(p), "r"(a) : "memory");
}
__device__ __forceinline__ void red_add1(uint32_t* p) { asm volatile("red.relaxed.gpu.global.add.u32 [%0],1;" ::"l"(p) : "memory"); }
__device__ __forceinline__ void sts128(uint32_t a, uint4 v) {
    asm volatile("st.shared.v4.u32 [%0],{%1,%2,%3,%4};" ::"r"(a), "r"(v.x), "r"(v.y), "r"(v.z), "r"(v.w) : "memory");
}
__device__ __forceinline__ uint4 lds128(uint32_t a) {
    uint4 v; asm volatile("ld.shared.v4.u32 {%0,%1,%2,%3},[%4];" : "=r"(v.x), "=r"(v.y), "=r"(v.z), "=r"(v.w) : "r"(a) : "memory");
    return v;
}
__device__ __forceinline__ void sts32f(uint32_t a, float v) { asm volatile("st.shared.f32 [%0],%1;" ::"r"(a), "f"(v) : "memory"); }
__device__ __forceinline__ float2 lds64f(uint32_t a) {
    float2 v; asm volatile("ld.shared.v2.f32 {%0,%1},[%2];" : "=f"(v.x), "=f"(v.y) : "r"(a) : "memory"); return v;
}
__device__ __forceinline__ void wg_fence() { asm volatile("wgmma.fence.sync.aligned;" ::: "memory"); }
__device__ __forceinline__ void wg_commit() { asm volatile("wgmma.commit_group.sync.aligned;" ::: "memory"); }
template <int N> __device__ __forceinline__ void wg_wait() { asm volatile("wgmma.wait_group.sync.aligned %0;" ::"n"(N) : "memory"); }
__device__ __forceinline__ uint64_t mk_desc(uint32_t addr, uint32_t lbo, uint32_t sbo) {
    return (uint64_t)((addr & 0x3FFFF) >> 4) | ((uint64_t)(lbo >> 4) << 16) | ((uint64_t)(sbo >> 4) << 32) | (1ull << 62);
}
__device__ __forceinline__ void wgmma_n32_rs(float (&d)[16], const uint32_t (&a)[4], uint64_t desc, int scale_d) {
    asm volatile("{.reg .pred p; setp.ne.b32 p,%21,0;\n"
                 "wgmma.mma_async.sync.aligned.m64n32k16.f32.bf16.bf16 "
                 "{%0,%1,%2,%3,%4,%5,%6,%7,%8,%9,%10,%11,%12,%13,%14,%15},{%16,%17,%18,%19},%20,p,1,1,0;}"
                 : "+f"(d[0]), "+f"(d[1]), "+f"(d[2]), "+f"(d[3]), "+f"(d[4]), "+f"(d[5]), "+f"(d[6]), "+f"(d[7]),
                   "+f"(d[8]), "+f"(d[9]), "+f"(d[10]), "+f"(d[11]), "+f"(d[12]), "+f"(d[13]), "+f"(d[14]), "+f"(d[15])
                 : "r"(a[0]), "r"(a[1]), "r"(a[2]), "r"(a[3]), "l"(desc), "r"(scale_d));
}
__device__ __forceinline__ void wgmma_n32_ss(float (&d)[16], uint64_t da, uint64_t desc) {
    asm volatile("wgmma.mma_async.sync.aligned.m64n32k16.f32.bf16.bf16 "
                 "{%0,%1,%2,%3,%4,%5,%6,%7,%8,%9,%10,%11,%12,%13,%14,%15},%16,%17,1,1,1,0,0;"
                 : "+f"(d[0]), "+f"(d[1]), "+f"(d[2]), "+f"(d[3]), "+f"(d[4]), "+f"(d[5]), "+f"(d[6]), "+f"(d[7]),
                   "+f"(d[8]), "+f"(d[9]), "+f"(d[10]), "+f"(d[11]), "+f"(d[12]), "+f"(d[13]), "+f"(d[14]), "+f"(d[15])
                 : "l"(da), "l"(desc));
}
__device__ __forceinline__ void pdl_wait() { asm volatile("griddepcontrol.wait;" ::: "memory"); }
__device__ __forceinline__ void pdl_launch() { asm volatile("griddepcontrol.launch_dependents;" ::: "memory"); }

__global__ void __launch_bounds__(256) k_pre(const __nv_bfloat16* __restrict__ x) {
    pdl_launch();
    const int warp = threadIdx.x >> 5, lane = threadIdx.x & 31;
    const int row = blockIdx.x * 8 + warp;
    const uint4* src = reinterpret_cast<const uint4*>(x + (size_t)row * DM);
    uint4 v[3];
    float f[24];
    float sum = 0.f;
#pragma unroll
    for (int i = 0; i < 3; i++) {
        int c = lane + 32 * i;
        v[i] = (c < 72) ? src[c] : make_uint4(0, 0, 0, 0);
        const uint32_t w[4] = {v[i].x, v[i].y, v[i].z, v[i].w};
#pragma unroll
        for (int j = 0; j < 4; j++) {
            f[i * 8 + 2 * j] = __uint_as_float(w[j] << 16);
            f[i * 8 + 2 * j + 1] = __uint_as_float(w[j] & 0xffff0000u);
            sum += f[i * 8 + 2 * j] + f[i * 8 + 2 * j + 1];
        }
    }
#pragma unroll
    for (int o = 16; o; o >>= 1) sum += __shfl_xor_sync(~0u, sum, o);
    const float mean = sum * (1.f / DM);
    float var = 0.f;
#pragma unroll
    for (int i = 0; i < 3; i++) {
        if (lane + 32 * i < 72) {
#pragma unroll
            for (int j = 0; j < 8; j++) { float d = f[i * 8 + j] - mean; var += d * d; }
        }
    }
#pragma unroll
    for (int o = 16; o; o >>= 1) var += __shfl_xor_sync(~0u, var, o);
    const float rstd = rsqrtf(var * (1.f / DM) + 1e-5f);
    const int seg = row >> 5, r = row & 31;
#pragma unroll
    for (int i = 0; i < 3; i++) {
        int c = lane + 32 * i;
        if (c < 72) {
            uint4 o;
            o.x = pack_bf16((f[i * 8 + 0] - mean) * rstd, (f[i * 8 + 1] - mean) * rstd);
            o.y = pack_bf16((f[i * 8 + 2] - mean) * rstd, (f[i * 8 + 3] - mean) * rstd);
            o.z = pack_bf16((f[i * 8 + 4] - mean) * rstd, (f[i * 8 + 5] - mean) * rstd);
            o.w = pack_bf16((f[i * 8 + 6] - mean) * rstd, (f[i * 8 + 7] - mean) * rstd);
            int kt = c >> 3, ch = c & 7;
            *reinterpret_cast<uint4*>(g_xn + (size_t)seg * XN_SEG_BYTES + kt * 4096 + r * 128 + ((ch ^ (r & 7)) << 4)) = o;
        }
    }
    if (blockIdx.x == 0 && threadIdx.x < 128) g_tab[threadIdx.x] = 0;
    if (blockIdx.x == 1 || (blockIdx.x == 2 && threadIdx.x < 16)) g_flag[(blockIdx.x - 1) * 256 + threadIdx.x] = 0;
}

constexpr int SM_XN = 0;
constexpr int SM_X = 73728;
constexpr int SM_MB = SM_X + 3 * 24576;
constexpr int SM_MEMT = SM_MB + 3 * 6144;
constexpr int SXR = 56;
constexpr int SM_SX = SM_MEMT + 9216;
constexpr int SM_SXX = SM_SX + 8 * SXR * 4;
constexpr int SM_OT = SM_SXX + 16 * SXR * 4;
constexpr int SM_OX = SM_OT + 2048;
constexpr int SM_MAIN_END = SM_OX + 4096;
constexpr int SM_STG_W = 0;
constexpr int SM_STG_WO = 147456;
constexpr int NREG_K = 33;
constexpr int SM_WS = 196608;
constexpr int SM_WO2 = SM_WS + (36 - NREG_K) * 4096;
constexpr int SM_BAR = SM_WO2 + 16384;
constexpr int SM_TIM = SM_BAR + 128;
constexpr int SM_CHAIN_BYTES = SM_TIM + 1024;
static_assert(SM_MAIN_END <= SM_WS, "smem");
static_assert(SM_CHAIN_BYTES <= 232448, "smem");
constexpr int BAR_MEM = 1, BAR_GO = 2, BAR_A = 3, BAR_B = 4, BAR_QD = 5;
#define BULK1 11

__device__ __forceinline__ uint32_t clk32() { uint32_t t; asm volatile("mov.u32 %0,%%clock;" : "=r"(t)::"memory"); return t; }
#define TSTAMP(i)
#define TFLUSH()
#define PIN(x) asm volatile("" : "+r"(x))
#define PINL(x) asm volatile("" : "+l"(x))

__device__ __forceinline__ uint2 ld_relaxed2(const void* p) {
    uint2 v;
    asm volatile("ld.relaxed.gpu.global.v2.u32 {%0,%1},[%2];" : "=r"(v.x), "=r"(v.y) : "l"(p) : "memory");
    return v;
}
__device__ __forceinline__ uint32_t ld_acquire1(const void* p) {
    uint32_t v; asm volatile("ld.acquire.gpu.global.u32 %0,[%1];" : "=r"(v) : "l"(p) : "memory"); return v;
}
__device__ __forceinline__ uint32_t xand(uint32_t a, uint32_t b, uint32_t m) {
    uint32_t r; asm("lop3.b32 %0,%1,%2,%3,0x42;" : "=r"(r) : "r"(a), "r"(b), "r"(m)); return r;
}
__device__ __forceinline__ uint32_t and3(uint32_t a, uint32_t b, uint32_t c) {
    uint32_t r; asm("lop3.b32 %0,%1,%2,%3,0x80;" : "=r"(r) : "r"(a), "r"(b), "r"(c)); return r;
}
__device__ __forceinline__ uint32_t settag(float v, uint32_t tag) {
    uint32_t r; asm("lop3.b32 %0,%1,0xfffffffe,%2,0xea;" : "=r"(r) : "r"(__float_as_uint(v)), "r"(tag)); return r;
}
__device__ __forceinline__ float rcp_fast(float x) { float r; asm("rcp.approx.ftz.f32 %0,%1;" : "=f"(r) : "f"(x)); return r; }
__device__ __forceinline__ void sts64f(uint32_t a, float x, float y) { asm volatile("st.shared.v2.f32 [%0],{%1,%2};" ::"r"(a), "f"(x), "f"(y) : "memory"); }

__device__ __forceinline__ uint32_t near_parity(uint8_t* blk, int cta) {
    uint32_t best[2] = {~0u, ~0u};
    uint8_t* a0 = blk + 0xC000 + 0x3000 + (cta & 31) * 128;
    st_relaxed1(a0, 0u);
    st_relaxed1(reinterpret_cast<uint8_t*>(reinterpret_cast<uintptr_t>(a0) ^ 0x1000), 0u);
    for (int r = 0; r < 3; r++)
#pragma unroll
        for (int p = 0; p < 2; p++) {
            uint8_t* a = reinterpret_cast<uint8_t*>(reinterpret_cast<uintptr_t>(a0) ^ (p << 12));
            uint32_t v, t1 = 0;
            const uint32_t t0 = clk32();
            asm volatile("atom.relaxed.gpu.global.add.u32 %0,[%1],1;" : "=r"(v) : "l"(a) : "memory");
            asm volatile("{.reg .pred p; setp.ne.u32 p,%1,0x7fffffff; @p mov.u32 %0,%%clock;}" : "+r"(t1) : "r"(v) : "memory");
            best[p] = min(best[p], t1 - t0);
        }
    return best[0] <= best[1] ? 0u : 1u;
}

template <int GRP>
__device__ __forceinline__ void xfinish(uint32_t sxa, uint32_t vaa, uint32_t vma, uint32_t st_w, uint32_t st_r, uint8_t* dst, int g, int t) {
    constexpr int NB = GRP + 2;
    constexpr bool needB = (GRP >= 2);
    const float sc = 0.08838834764831845f * 1.4426950408889634f;
    float2 v[6];
#pragma unroll
    for (int b = 0; b < NB + 1; b++) v[b] = lds64f(sxa + b * 32);
    uint32_t f0[4], f1[4];
    ldsm4(f0, vma);
    v[1].x += v[0].x; v[1].y += v[0].y;
    if (2 * t > g) v[NB].x = -INFINITY;
    if (2 * t + 1 > g) v[NB].y = -INFINITY;
    float mx = fmaxf(v[1].x, v[1].y);
#pragma unroll
    for (int b = 2; b < NB + 1; b++) mx = fmaxf(mx, fmaxf(v[b].x, v[b].y));
    mx = fmaxf(mx, __shfl_xor_sync(~0u, mx, 1));
    mx = fmaxf(mx, __shfl_xor_sync(~0u, mx, 2));
    mx *= sc;
    uint32_t pk[5];
    float sum = 0.f;
#pragma unroll
    for (int b = 0; b < 5; b++) {
        if (b < NB) {
            float p0 = ex2(fmaf(v[b + 1].x, sc, -mx)), p1 = ex2(fmaf(v[b + 1].y, sc, -mx));
            sum += p0 + p1;
            pk[b] = pack_bf16(p0, p1);
        } else pk[b] = 0u;
    }
    float o[2][4] = {{0.f, 0.f, 0.f, 0.f}, {0.f, 0.f, 0.f, 0.f}};
    ldsm4(f1, vaa);
    mma8(o[0], f0[0], f0[1], pk[0]);
    mma8(o[1], f0[2], f0[3], pk[0]);
    ldsm4(f0, vaa + 256);
    sum += __shfl_xor_sync(~0u, sum, 1);
    mma16(o[0], f1[0], f1[1], f1[2], f1[3], pk[1], pk[2]);
    if (needB) ldsm4(f1, vaa + 4096);
    mma16(o[1], f0[0], f0[1], f0[2], f0[3], pk[1], pk[2]);
    if (needB) ldsm4(f0, vaa + 4096 + 256);
    sum += __shfl_xor_sync(~0u, sum, 2);
    if (needB) {
        mma16(o[0], f1[0], f1[1], f1[2], f1[3], pk[3], pk[4]);
        mma16(o[1], f0[0], f0[1], f0[2], f0[3], pk[3], pk[4]);
    }
    const float s0 = __shfl_sync(~0u, sum, 8 * t), s1 = __shfl_sync(~0u, sum, 8 * t + 4);
    const float i0 = rcp_fast(s0), i1 = rcp_fast(s1);
    stsm4t(st_w, pack_bf16(o[0][0] * i0, o[0][1] * i1), pack_bf16(o[0][2] * i0, o[0][3] * i1),
           pack_bf16(o[1][0] * i0, o[1][1] * i1), pack_bf16(o[1][2] * i0, o[1][3] * i1));
    __syncwarp();
    uint4 val = lds128(st_r);
    *reinterpret_cast<uint4*>(dst + GRP * 1024) = val;
}

__device__ __forceinline__ void xattn(uint32_t sb, uint32_t xs, uint32_t mb, uint32_t barq, uint32_t phq, int c, int h, int s, int w, int lane, int& dead) {
    const int g = lane >> 2, t = lane & 3, m = lane >> 3, r = lane & 7;
    if (w < 2) {
        const int kt = (c == 2) ? 0 : w, grp = (c == 2) ? w : 3 - c;
        const uint32_t kb = xs + 8192 + (2 * kt + (m & 1)) * 2048 + (8 * (m >> 1) + r) * 16;
        const uint32_t qb = xs + grp * 2048 + lane * 16;
        float c0[4] = {0.f, 0.f, 0.f, 0.f}, c1[4] = {0.f, 0.f, 0.f, 0.f};
#pragma unroll
        for (int j = 0; j < 4; j++) {
            uint32_t q[4], a[4], b[4];
            ldsm4t(q, qb + j * 512);
            ldsm4t(a, kb + j * 512);
            ldsm4t(b, kb + j * 512 + 256);
            mma16(c0, a[0], a[1], a[2], a[3], q[0], q[1]);
            mma16(c1, b[0], b[1], b[2], b[3], q[2], q[3]);
        }
        const uint32_t p = sb + SM_SXX + (((grp & 1) * 8 + 2 * t) * SXR + 16 + 16 * kt + g) * 4;
        sts32f(p, c0[0] + c1[0]);
        sts32f(p + SXR * 4, c0[1] + c1[1]);
        sts32f(p + 32, c0[2] + c1[2]);
        sts32f(p + SXR * 4 + 32, c0[3] + c1[3]);
        mbar_wait(barq, phq, dead);
    } else {
        uint32_t qx[4][4];
        const uint32_t base = xs + ((c == 2 ? 0 : 2) + (m & 1)) * 2048 + ((w - 2) * 64 + 8 * (m >> 1) + r) * 16;
#pragma unroll
        for (int j = 0; j < 4; j++) ldsm4t(qx[j], base + j * 256);
        mbar_wait(barq, phq, dead);
        float c2[4] = {0.f, 0.f, 0.f, 0.f}, c3[4] = {0.f, 0.f, 0.f, 0.f};
#pragma unroll
        for (int j = 0; j < 2; j++) {
            uint32_t a[4];
            ldsm4t(a, mb + 2048 + (w - 2) * 1024 + j * 512 + lane * 16);
            mma16(c2, qx[2 * j][0], qx[2 * j][1], qx[2 * j][2], qx[2 * j][3], a[0], a[1]);
            mma16(c3, qx[2 * j + 1][0], qx[2 * j + 1][1], qx[2 * j + 1][2], qx[2 * j + 1][3], a[2], a[3]);
        }
        const uint32_t sxx = sb + SM_SXX + (g * SXR + 8 * (w - 2) + 2 * t) * 4;
        sts64f(sxx, c2[0] + c3[0], c2[1] + c3[1]);
        sts64f(sxx + 8 * SXR * 4, c2[2] + c3[2], c2[3] + c3[3]);
    }
    bar_sync(BAR_A, 128);
    const uint32_t sxa = sb + SM_SXX + (g * SXR + 2 * t) * 4;
    const uint32_t vaa = xs + 16384 + (m >> 1) * 2048 + (32 * w + 8 * (m & 1) + r) * 16;
    const uint32_t vma = mb + 4096 + (32 * w + lane) * 16;
    const uint32_t st_w = sb + SM_OX + w * 512 + r * 64 + ((m ^ ((r >> 1) & 3)) << 4);
    const uint32_t st_r = sb + SM_OX + w * 512 + g * 64 + ((t ^ ((g >> 1) & 3)) << 4);
    uint8_t* dst = g_ox + (size_t)((s >> 2) * 64 + 2 * h + (w >> 1)) * 16384 + ((s & 3) * 32 + g) * 128 + ((((w & 1) * 4 + t) ^ g) << 4);
    if (c == 2) {
        xfinish<1>(sxa + 8 * SXR * 4, vaa, vma, st_w, st_r, dst, g, t);
        xfinish<0>(sxa, vaa, vma, st_w + 2048, st_r + 2048, dst, g, t);
    } else if (c == 0) xfinish<3>(sxa + 8 * SXR * 4, vaa, vma, st_w, st_r, dst, g, t);
    else xfinish<2>(sxa, vaa, vma, st_w, st_r, dst, g, t);
}

#define REGS_A 176
#define POLL_MODE 0
#define DELAY1 300
#define STAG1 200
#define DELAY2 200
#define STAG2 200
#define DELAY2N 900

__global__ void __cluster_dims__(3, 1, 1) __launch_bounds__(384, 1)
k_chain(const __nv_bfloat16* __restrict__ mem0, const __nv_bfloat16* __restrict__ Wq, const __nv_bfloat16* __restrict__ Wk,
        const __nv_bfloat16* __restrict__ Wv, const __nv_bfloat16* __restrict__ Wo) {
    extern __shared__ __align__(1024) uint8_t smem[];
    const uint32_t sb = smem_u32(smem);
    const int tid = threadIdx.x, lane = tid & 31;
    const int warp = __shfl_sync(~0u, tid >> 5, 0);
    const int c = blockIdx.x % 3, h = blockIdx.x / 3;
    const uint32_t bar_qm = sb + SM_BAR, bar_x = sb + SM_BAR + 24, bar_xn = sb + SM_BAR + 48;
    int dead = 0;

    {
        const __nv_bfloat16* W = (c == 0 ? Wq : (c == 1 ? Wk : Wv)) + h * DH;
#pragma unroll 4
        for (int i = tid; i < 576 * 16; i += 384) {
            int k = i >> 4, ch = i & 15;
            cp_async16(sb + SM_STG_W + k * 256 + ((ch ^ (k & 7)) << 4), W + (size_t)k * HD + ch * 8);
        }
        const __nv_bfloat16* Wos = Wo + (size_t)h * DH * DM + c * 192;
#pragma unroll 4
        for (int i = tid; i < 128 * 24; i += 384) {
            int k = i / 24, ch = i % 24;
            cp_async16(sb + SM_STG_WO + k * 384 + ((ch ^ (k & 7)) << 4), Wos + (size_t)k * DM + ch * 8);
        }
        asm volatile("cp.async.commit_group;" ::: "memory");
        if (tid == 0) {
            for (int i = 0; i < 8; i++) mbar_init(bar_qm + 8 * i, 1);
            asm volatile("fence.mbarrier_init.release.cluster;" ::: "memory");
        }
        asm volatile("cp.async.wait_group 0;" ::: "memory");
        __syncthreads();
    }
    auto ship_x = [&](int sl) {
        const uint32_t src = sb + SM_X + sl * 24576 + c * 8192, bx = bar_x + sl * 8;
        const uint32_t p1 = (c + 1) % 3, p2 = (c + 2) % 3;
        bulk_s2s(mapa(src, p1), src, 8192, mapa(bx, p1));
        bulk_s2s(mapa(src, p2), src, 8192, mapa(bx, p2));
        mbar_expect_tx(bx, 16384);
    };
    auto load_xn = [&](int seg) {
        const int b = seg & 1;
        mbar_expect_tx(bar_xn + 8 * b, XN_SEG_BYTES);
        bulk_g2s_mc(sb + SM_XN + b * XN_SEG_BYTES + c * 12288, g_xn + (size_t)seg * XN_SEG_BYTES + c * 12288, 12288, bar_xn + 8 * b, 7);
    };

    if (warp < 8) {
        asm volatile("setmaxnreg.inc.sync.aligned.u32 %0;" ::"n"(REGS_A));
        uint32_t W[NREG_K][4];
        {
            const int m = lane >> 3, r = lane & 7;
#pragma unroll
            for (int j = 0; j < 36; j++) {
                int k = 16 * j + 8 * (m >> 1) + r, ch = 2 * warp + (m & 1);
                if (j < NREG_K) ldsm4t(W[j], sb + SM_STG_W + k * 256 + ((ch ^ (k & 7)) << 4));
                else {
                    uint32_t f[4];
                    ldsm4t(f, sb + SM_STG_W + k * 256 + ((ch ^ (k & 7)) << 4));
                    stsm4(sb + SM_WS + (j - NREG_K) * 4096 + (m >> 1) * 2048 + (2 * warp + (m & 1)) * 128 + r * 16, f[0], f[1], f[2], f[3]);
                }
            }
            fence_async();
        }
        cluster_sync();
        const uint32_t rb0 = mapa(sb, 0), rb1 = mapa(sb, 1), rb2 = mapa(sb, 2);
        int slot = 0, ph3 = 0;
        for (int s = -2; s < NSEG; s++) {
            const int sl = slot == 2 ? 0 : slot + 1;
            int lane;
            asm volatile("mov.u32 %0,%%laneid;" : "=r"(lane));
            if (s >= 0) {
                uint32_t WS[36 - NREG_K][4];
                {
                    const uint32_t a = sb + SM_WS + ((lane >> 4) & 1) * 2048 + (2 * warp + ((lane >> 3) & 1)) * 128 + (lane & 7) * 16;
#pragma unroll
                    for (int j = 0; j < 36 - NREG_K; j++) ldsm4(WS[j], a + j * 4096);
                }
                const uint32_t doff = SM_MB + c * 2048 + (16 * warp + (lane >> 2)) * 16 + (lane & 3) * 4 + sl * 6144;
                const uint32_t ma = sb + SM_MEMT + lane * 16;
                bar_sync(BAR_MEM, 384);
                float a0[4] = {0.f, 0.f, 0.f, 0.f}, a1[4] = {0.f, 0.f, 0.f, 0.f}, a2[4] = {0.f, 0.f, 0.f, 0.f};
                uint32_t b[3][4];
                ldsm4t(b[0], ma + 16 * 512);
                ldsm4t(b[1], ma + 17 * 512);
                TSTAMP(0);
#pragma unroll
                for (int jj = 0; jj < 18; jj++) {
                    const int j = (jj + 16) % 18;
                    if (jj + 2 < 18) ldsm4t(b[(jj + 2) % 3], ma + ((jj + 18) % 18) * 512);
                    const uint32_t(&bb)[4] = b[jj % 3];
                    float(&c0)[4] = (2 * jj) % 3 == 0 ? a0 : ((2 * jj) % 3 == 1 ? a1 : a2);
                    float(&c1)[4] = (2 * jj + 1) % 3 == 0 ? a0 : ((2 * jj + 1) % 3 == 1 ? a1 : a2);
                    if (2 * j < NREG_K) mma16(c0, W[2 * j][0], W[2 * j][1], W[2 * j][2], W[2 * j][3], bb[0], bb[1]);
                    else mma16(c0, WS[2 * j - NREG_K][0], WS[2 * j - NREG_K][1], WS[2 * j - NREG_K][2], WS[2 * j - NREG_K][3], bb[0], bb[1]);
                    if (2 * j + 1 < NREG_K) mma16(c1, W[2 * j + 1][0], W[2 * j + 1][1], W[2 * j + 1][2], W[2 * j + 1][3], bb[2], bb[3]);
                    else mma16(c1, WS[2 * j + 1 - NREG_K][0], WS[2 * j + 1 - NREG_K][1], WS[2 * j + 1 - NREG_K][2], WS[2 * j + 1 - NREG_K][3], bb[2], bb[3]);
                }
                const uint32_t w0 = pack_bf16(a0[0] + a1[0] + a2[0], a0[1] + a1[1] + a2[1]);
                const uint32_t w1 = pack_bf16(a0[2] + a1[2] + a2[2], a0[3] + a1[3] + a2[3]);
                const uint32_t boff = SM_BAR + sl * 8;
                st_async32(rb0 + doff, w0, rb0 + boff); st_async32(rb1 + doff, w0, rb1 + boff); st_async32(rb2 + doff, w0, rb2 + boff);
                st_async32(rb0 + doff + 128, w1, rb0 + boff); st_async32(rb1 + doff + 128, w1, rb1 + boff); st_async32(rb2 + doff + 128, w1, rb2 + boff);
                bar_arrive(BAR_QD, 352);
                TSTAMP(1);
            }
            const int sn = s + 2;
            const bool bulk = sn < NSEG;
            const uint64_t desc0 = mk_desc(sb + SM_XN + (sn & 1) * XN_SEG_BYTES, 16, 1024);
            const uint64_t da = (uint64_t)(((sb + SM_WS + (warp >> 2) * 1024) & 0x3FFFF) >> 4) | (128ull << 16) | (8ull << 32);
            float acc[16];
            if (warp < 4) {
                if (s == NSEG - 1) break;
                if (bulk) {
                    mbar_wait(bar_xn + (sn & 1) * 8, (sn >> 1) & 1, dead);
                    wg_fence();
#pragma unroll
                    for (int j = 0; j < BULK1; j++) wgmma_n32_rs(acc, W[j], desc0 + (uint64_t)(((j >> 2) * 4096 + (j & 3) * 32) >> 4), j > 0);
                    wg_commit();
                    wg_wait<0>();
                }
                TSTAMP(2);
                if (s >= 0) {
                    if (warp == 0) {
                        mbar_wait(bar_qm + sl * 8, ph3, dead);
                        if (lane == 0) {
                            if (s + 3 < NSEG) load_xn(s + 3);
                        }
                        __syncwarp();
                        TSTAMP(5);
                    }
                    bar_sync(BAR_GO, 384);
                }
                if (bulk) {
                    wg_fence();
#pragma unroll
                    for (int j = BULK1; j < NREG_K; j++) wgmma_n32_rs(acc, W[j], desc0 + (uint64_t)(((j >> 2) * 4096 + (j & 3) * 32) >> 4), j > 0);
#pragma unroll
                    for (int j = NREG_K; j < 36; j++)
                        wgmma_n32_ss(acc, da + (uint64_t)((j - NREG_K) * 256), desc0 + (uint64_t)(((j >> 2) * 4096 + (j & 3) * 32) >> 4));
                    wg_commit();
                    wg_wait<0>();
                }
            } else {
                if (s >= 0) {
                    mbar_wait(bar_x + sl * 8, ph3, dead);
                    xattn(sb, sb + SM_X + sl * 24576, sb + SM_MB + sl * 6144, bar_qm + sl * 8, ph3, c, h, s, warp - 4, lane, dead);
                    TSTAMP(2);
                    if (s == NSEG - 1) {
                        bar_sync(BAR_A, 128);
                        if (tid == 128) { asm volatile("fence.acq_rel.gpu;" ::: "memory"); red_add1(g_flag + 15 * 16 + FL_OX); }
                        break;
                    }
                    bar_sync(BAR_GO, 384);
                }
                if (bulk) {
                    mbar_wait(bar_xn + (sn & 1) * 8, (sn >> 1) & 1, dead);
                    wg_fence();
#pragma unroll
                    for (int j = 0; j < NREG_K; j++) wgmma_n32_rs(acc, W[j], desc0 + (uint64_t)(((j >> 2) * 4096 + (j & 3) * 32) >> 4), j > 0);
#pragma unroll
                    for (int j = NREG_K; j < 36; j++)
                        wgmma_n32_ss(acc, da + (uint64_t)((j - NREG_K) * 256), desc0 + (uint64_t)(((j >> 2) * 4096 + (j & 3) * 32) >> 4));
                    wg_commit();
                    wg_wait<0>();
                }
            }
            TSTAMP(3);
            if (bulk) {
                const uint32_t xo = sb + SM_X + slot * 24576 + c * 8192 + ((lane >> 4) & 1) * 2048 + (16 * warp + 8 * ((lane >> 3) & 1) + (lane & 7)) * 16;
                stsm4(xo, pack_bf16(acc[0], acc[1]), pack_bf16(acc[2], acc[3]), pack_bf16(acc[4], acc[5]), pack_bf16(acc[6], acc[7]));
                stsm4(xo + 4096, pack_bf16(acc[8], acc[9]), pack_bf16(acc[10], acc[11]), pack_bf16(acc[12], acc[13]), pack_bf16(acc[14], acc[15]));
                fence_async();
            }
            if (s == -2) bar_arrive(BAR_GO, 384);
            TSTAMP(4);
            if (s >= 0) { TFLUSH(); }
            if (sl == 2 && s >= 0) ph3 ^= 1;
            slot = sl;
        }
        cluster_sync();
    } else {
        asm volatile("setmaxnreg.dec.sync.aligned.u32 %0;" ::"n"(504 - 2 * REGS_A));
        const int w = warp - 8, bt = tid - 256;
        const int g = lane >> 2, t = lane & 3, m = lane >> 3, r = lane & 7;
        const int cta = blockIdx.x;
        uint32_t WO[2][8][4];
#pragma unroll
        for (int i = 0; i < 3; i++)
#pragma unroll
            for (int j = 0; j < 8; j++) {
                int k = 16 * j + 8 * (m >> 1) + r, ch = 2 * (3 * w + i) + (m & 1);
                if (i < 2) ldsm4t(WO[i][j], sb + SM_STG_WO + k * 384 + ((ch ^ (k & 7)) << 4));
                else {
                    uint32_t f[4];
                    ldsm4t(f, sb + SM_STG_WO + k * 384 + ((ch ^ (k & 7)) << 4));
                    stsm4(sb + SM_WO2 + w * 4096 + j * 512 + lane * 16, f[0], f[1], f[2], f[3]);
                }
            }
        cluster_sync();
        pdl_wait();
        if (bt == 0) {
            asm volatile("fence.acq_rel.gpu;" ::: "memory");
            pdl_launch();
            fence_async();
            load_xn(0);
            load_xn(1);
        }
        for (int i = bt; i < 8 * DM; i += 128) {
            int row = i / DM, col = i % DM;
            *reinterpret_cast<__nv_bfloat16*>(smem + SM_MEMT + col * 16 + row * 2) = mem0[i];
        }
        uint8_t* const xb = reinterpret_cast<uint8_t*>((reinterpret_cast<uintptr_t>(g_xch) + 65535) & ~(uintptr_t)65535);
        uint8_t* const c2b = xb + (size_t)NOWN * 65536;
        uint32_t pinfo;
        {
            volatile uint32_t* sp = reinterpret_cast<volatile uint32_t*>(smem + SM_TIM + 900);
            if (lane == 0 && w < 3) sp[w] = near_parity(w == 0 ? xb + (size_t)(cta < NOWN ? cta : 0) * 65536 : c2b + (w - 1) * 65536, cta);
            bar_sync(BAR_B, 128);
            const uint32_t par1 = sp[0];
            pinfo = sp[1] | (sp[2] << 1) | (par1 << 2);
            if (cta < NOWN) {
                uint8_t* blk = xb + (size_t)cta * 65536 + par1 * 4096;
                for (int i = bt; i < 1024; i += 128) *reinterpret_cast<uint4*>(blk + (i >> 8) * 16384 + (i & 255) * 16) = make_uint4(0, 0, 0, 0);
                const int o = cta * 128;
                if (bt < 64) *reinterpret_cast<uint4*>(c2b + (bt >> 5) * 65536 + ((bt >> 3) & 3) * 4096 + (o >> 12) * 16384 + (o & 4095) + (bt & 7) * 16) = make_uint4(0, 0, 0, 0);
                __threadfence();
                bar_sync(BAR_B, 128);
                if (bt == 0) st_relaxed1(g_tab + cta, 1u + par1);
            }
            uint32_t tv = 1;
            if (bt < NOWN) {
                int n = 0;
                while ((tv = ld_acquire1(g_tab + bt)) == 0u) { if (++n > SPIN_LIMIT) { dead = 1; break; } }
                reinterpret_cast<volatile uint8_t*>(smem + SM_TIM + 800)[bt] = (uint8_t)(tv - 1);
            }
            bar_sync(BAR_B, 128);
#pragma unroll
            for (int i = 0; i < 6; i++)
                pinfo |= (uint32_t)(reinterpret_cast<volatile uint8_t*>(smem + SM_TIM + 800)[c * 24 + w * 6 + i] & 1) << (12 + i);
            pinfo = __shfl_sync(~0u, pinfo, 0);
            dead = __any_sync(~0u, dead);
        }
        bar_sync(BAR_GO, 384);
        if (bt == 0) {
            ship_x(0);
            mbar_wait(bar_x, 0, dead);
            load_xn(2);
        }
        __syncwarp();
        bar_arrive(BAR_MEM, 384);
        const float sc = 0.08838834764831845f * 1.4426950408889634f;
        int slot = 0, ph3 = 0;
        for (int s = 0; s < NSEG; s++) {
            int lane;
            asm volatile("mov.u32 %0,%%laneid;" : "=r"(lane));
            const int g = lane >> 2, t = lane & 3, m = lane >> 3, r = lane & 7, bt = w * 32 + lane;
            const uint32_t xs = sb + SM_X + slot * 24576;
            const uint32_t mb = sb + SM_MB + slot * 6144;
            if (bt == 64) mbar_expect_tx(bar_qm + slot * 8, 6144);
            if (s == NSEG - 1) { if (w < 3) bar_arrive(BAR_QD, 352); break; }
            mbar_wait(bar_x + slot * 8, ph3, dead);
            const uint32_t tag = ((s >> 1) & 1) ^ 1;
            const uint32_t vaa = xs + 16384 + (m >> 1) * 2048 + (32 * w + 8 * (m & 1) + r) * 16;
            const uint32_t vma = mb + 4096 + (32 * w + lane) * 16;
            const uint32_t sxr = sb + SM_SX + (g * SXR + 2 * t) * 4;
            const uint32_t l16 = sb + lane * 16;
            uint32_t W2[8][4];
            if (w < 3) bar_sync(BAR_QD, 352);
            if (bt == 64) {
                ship_x(slot == 2 ? 0 : slot + 1);
            }
            __syncwarp();
            TSTAMP(0);
            if (w < 2) {
                uint32_t kf[8][4];
                const uint32_t base = xs + 8192 + (2 * w + (m & 1)) * 2048 + (8 * (m >> 1) + r) * 16;
#pragma unroll
                for (int j = 0; j < 8; j++) ldsm4t(kf[j], base + j * 256);
                const uint32_t sxw = sb + SM_SX + ((2 * t) * SXR + 16 + 16 * w + g) * 4;
                const uint32_t qa = mb + lane * 16;
                TSTAMP(1);
                mbar_wait(bar_qm + slot * 8, ph3, dead);
                uint32_t q[4][4];
#pragma unroll
                for (int j = 0; j < 4; j++) ldsm4t(q[j], qa + j * 512);
                TSTAMP(2);
                float c0[4] = {0.f, 0.f, 0.f, 0.f}, c1[4] = {0.f, 0.f, 0.f, 0.f}, c2[4] = {0.f, 0.f, 0.f, 0.f};
#pragma unroll
                for (int j = 0; j < 8; j++) {
                    float(&cc)[4] = j % 3 == 0 ? c0 : (j % 3 == 1 ? c1 : c2);
                    mma16(cc, kf[j][0], kf[j][1], kf[j][2], kf[j][3], q[j >> 1][(j & 1) * 2], q[j >> 1][(j & 1) * 2 + 1]);
                }
                sts32f(sxw, (c2[0] + c0[0]) + c1[0]);
                sts32f(sxw + SXR * 4, (c2[1] + c0[1]) + c1[1]);
                sts32f(sxw + 32, (c2[2] + c0[2]) + c1[2]);
                sts32f(sxw + SXR * 4 + 32, (c2[3] + c0[3]) + c1[3]);
#pragma unroll
                for (int j = 0; j < 8; j++) ldsm4(W2[j], l16 + SM_WO2 + w * 4096 + j * 512);
            } else {
#pragma unroll
                for (int j = 0; j < 8; j++) ldsm4(W2[j], l16 + SM_WO2 + w * 4096 + j * 512);
                const uint32_t qa = mb + (w - 2) * 1024 + ((((m & 1) << 1) | (m >> 1)) * 8 + r) * 16;
                const uint32_t ka = mb + 2048 + (w - 2) * 1024 + lane * 16;
                const uint32_t sxw = sb + SM_SX + ((2 * t) * SXR + 8 * (w - 2) + g) * 4;
                TSTAMP(1);
                mbar_wait(bar_qm + slot * 8, ph3, dead);
                uint32_t q[2][4], a[2][4];
                ldsm4t(q[0], qa); ldsm4t(a[0], ka); ldsm4t(q[1], qa + 512); ldsm4t(a[1], ka + 512);
                TSTAMP(2);
                float c0[4] = {0.f, 0.f, 0.f, 0.f}, c1[4] = {0.f, 0.f, 0.f, 0.f};
#pragma unroll
                for (int j = 0; j < 2; j++) {
                    mma16(c0, a[j][0], a[j][1], a[j][2], a[j][3], q[j][0], q[j][1]);
                    mma16(c1, a[j][0], a[j][1], a[j][2], a[j][3], q[j][2], q[j][3]);
                }
                sts32f(sxw, c0[0] + c1[2]);
                sts32f(sxw + SXR * 4, c0[1] + c1[3]);
            }
            bar_sync(BAR_B, 128);
            float2 v[6];
#pragma unroll
            for (int b = 0; b < 6; b++) v[b] = lds64f(sxr + b * 32);
            TSTAMP(3);
            uint32_t va[2][2][4], vmm[4];
            ldsm4(vmm, vma);
            ldsm4(va[0][0], vaa); ldsm4(va[1][0], vaa + 256); ldsm4(va[0][1], vaa + 4096); ldsm4(va[1][1], vaa + 4096 + 256);
            v[1].x += v[0].x; v[1].y += v[0].y;
            float mx = fmaxf(fmaxf(fmaxf(v[2].x, v[2].y), fmaxf(v[3].x, v[3].y)), fmaxf(fmaxf(v[4].x, v[4].y), fmaxf(v[5].x, v[5].y)));
            mx = fmaxf(mx, fmaxf(v[1].x, v[1].y));
            mx = fmaxf(mx, __shfl_xor_sync(~0u, mx, 1));
            mx = fmaxf(mx, __shfl_xor_sync(~0u, mx, 2));
            mx *= sc;
            float o[2][4] = {{0.f, 0.f, 0.f, 0.f}, {0.f, 0.f, 0.f, 0.f}};
            float e[10];
#pragma unroll
            for (int b = 0; b < 5; b++) { e[2 * b] = ex2(fmaf(v[b + 1].x, sc, -mx)); e[2 * b + 1] = ex2(fmaf(v[b + 1].y, sc, -mx)); }
            {
                const uint32_t pk0 = pack_bf16(e[0], e[1]);
                mma8(o[0], vmm[0], vmm[1], pk0);
                mma8(o[1], vmm[2], vmm[3], pk0);
                const uint32_t pk1 = pack_bf16(e[2], e[3]), pk2 = pack_bf16(e[4], e[5]);
                mma16(o[0], va[0][0][0], va[0][0][1], va[0][0][2], va[0][0][3], pk1, pk2);
                mma16(o[1], va[1][0][0], va[1][0][1], va[1][0][2], va[1][0][3], pk1, pk2);
                const uint32_t pk3 = pack_bf16(e[6], e[7]), pk4 = pack_bf16(e[8], e[9]);
                mma16(o[0], va[0][1][0], va[0][1][1], va[0][1][2], va[0][1][3], pk3, pk4);
                mma16(o[1], va[1][1][0], va[1][1][1], va[1][1][2], va[1][1][3], pk3, pk4);
            }
            float sum = ((e[0] + e[1]) + (e[2] + e[3])) + ((e[4] + e[5]) + (e[6] + e[7])) + (e[8] + e[9]);
            sum += __shfl_xor_sync(~0u, sum, 1);
            stsm4(l16 + SM_OT + w * 512, pack_bf16(o[0][0], o[0][1]), pack_bf16(o[0][2], o[0][3]), pack_bf16(o[1][0], o[1][1]), pack_bf16(o[1][2], o[1][3]));
            TSTAMP(4);
            bar_sync(BAR_B, 128);
            uint32_t ob[4][4];
#pragma unroll
            for (int j = 0; j < 4; j++) ldsm4t(ob[j], l16 + SM_OT + j * 512);
            TSTAMP(5);
            sum += __shfl_xor_sync(~0u, sum, 2);
            float d[3][4];
#pragma unroll
            for (int i = 0; i < 3; i++) { d[i][0] = d[i][1] = d[i][2] = d[i][3] = 0.f; }
            float i0 = 0.f, i1 = 0.f;
#pragma unroll
            for (int j = 0; j < 8; j++) {
                const uint32_t b0 = ob[j >> 1][(j & 1) * 2], b1 = ob[j >> 1][(j & 1) * 2 + 1];
                mma16(d[0], WO[0][j][0], WO[0][j][1], WO[0][j][2], WO[0][j][3], b0, b1);
                mma16(d[1], WO[1][j][0], WO[1][j][1], WO[1][j][2], WO[1][j][3], b0, b1);
                mma16(d[2], W2[j][0], W2[j][1], W2[j][2], W2[j][3], b0, b1);
                if (j == 1) {
                    const float inv = rcp_fast(sum);
                    i0 = __shfl_sync(~0u, inv, 8 * t); i1 = __shfl_sync(~0u, inv, 8 * t + 4);
                }
            }
            {
                uint8_t* p1 = xb + ((c * 24 + w * 6) * 65536 + (s & 1) * 32768 + (h >> 4) * 16384 + (h & 15) * 256) + lane * 8;
#pragma unroll
                for (int i = 0; i < 3; i++) {
                    st_relaxed2(p1 + ((pinfo >> (2 * i)) & 4096u) + (2 * i) * 65536, settag(d[i][0] * i0, tag), settag(d[i][1] * i1, tag));
                    st_relaxed2(p1 + ((pinfo >> (2 * i + 1)) & 4096u) + (2 * i + 1) * 65536, settag(d[i][2] * i0, tag), settag(d[i][3] * i1, tag));
                }
            }
            const uint32_t t_st = clk32();
            bar_arrive(BAR_GO, 384);
            TSTAMP(6);
            const uint8_t* src2 = c2b + ((s >> 1) & 1) * 65536 + ((s & 1) * 0x3000 ^ (((pinfo >> ((s >> 1) & 1)) & 1) << 12)) + bt * 16;
            const uint32_t mt = sb + SM_MEMT + bt * 16;
            uint32_t t_pub = t_st + DELAY2N;
            if (cta < NOWN) {
                const uint8_t* src = xb + (cta * 65536 + (pinfo & 4u) * 1024 + (s & 1) * 32768 + w * 64) + ((lane >> 4) * 16384 + ((lane >> 3) & 1) * 2048 + r * 8);
                const int o = cta * 128 + w * 32 + r * 4;
                const uint32_t o_pub = NOWN * 65536 + (m & 1) * 0x1000 + (o >> 12) * 16384 + (o & 4095);
                const int rs = s - (lane >> 4);
                uint8_t* dst = xb + (o_pub + ((rs >> 1) & 1) * 65536 + (rs & 1) * 0x2000);
                dst = reinterpret_cast<uint8_t*>(__shfl_sync(~0u, reinterpret_cast<unsigned long long>(dst), lane));
                const uint32_t msk = tag ^ 1u;
                uint2 v2[8];
                uint32_t x[8];
#pragma unroll
                for (int i = 0; i < 8; i++) { x[i] = 0u; v2[i] = make_uint2(0u, 0u); }
                while ((int)(clk32() - t_st) < DELAY1);
                TSTAMP(7);
                int n = 0;
                while (true) {
#pragma unroll
                    for (int i = 0; i < 8; i++) if (!(x[i] & 1u)) v2[i] = ld_relaxed2(src + i * 256);
#pragma unroll
                    for (int i = 0; i < 8; i++) x[i] = xand(v2[i].x, v2[i].y, msk);
                    float k0 = ((__uint_as_float(v2[0].x) + __uint_as_float(v2[1].x)) + (__uint_as_float(v2[2].x) + __uint_as_float(v2[3].x))) +
                               ((__uint_as_float(v2[4].x) + __uint_as_float(v2[5].x)) + (__uint_as_float(v2[6].x) + __uint_as_float(v2[7].x)));
                    float k1 = ((__uint_as_float(v2[0].y) + __uint_as_float(v2[1].y)) + (__uint_as_float(v2[2].y) + __uint_as_float(v2[3].y))) +
                               ((__uint_as_float(v2[4].y) + __uint_as_float(v2[5].y)) + (__uint_as_float(v2[6].y) + __uint_as_float(v2[7].y)));
                    const uint32_t ok = and3(and3(x[0], x[1], x[2]), and3(x[3], x[4], x[5]), x[6] & x[7]) & 1u;
                    k0 += __shfl_xor_sync(~0u, k0, 8);
                    k1 += __shfl_xor_sync(~0u, k1, 8);
                    const bool all = __all_sync(~0u, (ok | dead) != 0);
                    k0 += __shfl_xor_sync(~0u, k0, 16);
                    k1 += __shfl_xor_sync(~0u, k1, 16);
                    uint32_t word = pack_bf16(k0, k1);
                    if (word == 0u) word = 0x80000000u;
                    if (lane & 16) word = 0u;
                    if (all) { st_relaxed1(dst, word); break; }
                    if (++n > SPIN_LIMIT) dead = 1;
                }
                t_pub = clk32();
            }
            TSTAMP(8);
            {
                uint4 v4[5];
                uint32_t ok[5];
#pragma unroll
                for (int i = 0; i < 5; i++) { ok[i] = (i == 4 && w >= 2) ? 1u : 0u; v4[i] = make_uint4(1, 1, 1, 1); }
                while ((int)(clk32() - t_pub) < DELAY2);
                int n = 0;
                while (true) {
#pragma unroll
                    for (int i = 0; i < 5; i++) if (!ok[i]) v4[i] = ld_relaxed4(src2 + (i & 1) * 2048 + (i >> 1) * 16384);
#pragma unroll
                    for (int i = 0; i < 5; i++) if (!ok[i]) sts128(mt + i * 2048, v4[i]);
#pragma unroll
                    for (int i = 0; i < 5; i++) ok[i] = min(__vimin3_u32(v4[i].x, v4[i].y, v4[i].z), v4[i].w);
                    const uint32_t all = min(__vimin3_u32(ok[0], ok[1], ok[2]), min(ok[3], ok[4]));
                    if (__all_sync(~0u, (all | dead) != 0)) break;
                    if (++n > SPIN_LIMIT) dead = 1;
                }
                bar_arrive(BAR_MEM, 384);
            }
            TSTAMP(9);
            if (w == 3) {
                asm volatile("fence.acq_rel.gpu;" ::: "memory");
                if ((s & 3) == 0 && s > 0 && lane == 0) red_add1(g_flag + ((s >> 2) - 1) * 16 + FL_OX);
            }
            TSTAMP(10);
            TFLUSH();
            if (slot == 2) { slot = 0; ph3 ^= 1; } else slot++;
        }
        cluster_sync();
    }
}

constexpr int G_ST = 4;
constexpr int G_STAGE = 16384 + 24576;
constexpr int T_STG = G_ST * G_STAGE;
constexpr int T_AUX = T_STG + 49152;
constexpr int T_B2 = T_AUX + 2 * 4608;
constexpr int T_BAR = T_B2 + 2304;
constexpr int T_SMEM = T_BAR + 256 + 1024;
constexpr int NINIT = 36;
__host__ __device__ constexpr int ks_w(int rb) { return rb == 0 ? 8 : (rb < 12 ? 2 : (rb < 15 ? 4 : 12)); }
__host__ __device__ constexpr int ks_f(int rb) { return rb < 8 ? 2 : (rb < 14 ? 4 : (rb < 15 ? 8 : 11)); }
__host__ __device__ constexpr int kpart(int total, int ks) { return ks == 2 ? total / 2 - 4 : (ks == 4 ? total / 4 - 2 : (ks == 8 ? total / 8 - 1 : total / ks)); }

__device__ __forceinline__ void tma2d(uint32_t dst, const CUtensorMap* tm, int c0, int c1, uint32_t bar) {
    asm volatile("cp.async.bulk.tensor.2d.shared::cluster.global.mbarrier::complete_tx::bytes [%0],[%1,{%3,%4}],[%2];"
                 ::"r"(dst), "l"(tm), "r"(bar), "r"(c0), "r"(c1) : "memory");
}
__device__ __forceinline__ void wgmma_n192_ss(float (&d)[96], uint64_t da, uint64_t db, int scale_d) {
    asm volatile("{.reg .pred p; setp.ne.b32 p,%98,0;\n"
                 "wgmma.mma_async.sync.aligned.m64n192k16.f32.bf16.bf16 {"
                 "%0,%1,%2,%3,%4,%5,%6,%7,%8,%9,%10,%11,%12,%13,%14,%15,%16,%17,%18,%19,%20,%21,%22,%23,"
                 "%24,%25,%26,%27,%28,%29,%30,%31,%32,%33,%34,%35,%36,%37,%38,%39,%40,%41,%42,%43,%44,%45,%46,%47,"
                 "%48,%49,%50,%51,%52,%53,%54,%55,%56,%57,%58,%59,%60,%61,%62,%63,%64,%65,%66,%67,%68,%69,%70,%71,"
                 "%72,%73,%74,%75,%76,%77,%78,%79,%80,%81,%82,%83,%84,%85,%86,%87,%88,%89,%90,%91,%92,%93,%94,%95},"
                 "%96,%97,p,1,1,0,1;}"
                 : "+f"(d[0]), "+f"(d[1]), "+f"(d[2]), "+f"(d[3]), "+f"(d[4]), "+f"(d[5]), "+f"(d[6]), "+f"(d[7]),
                   "+f"(d[8]), "+f"(d[9]), "+f"(d[10]), "+f"(d[11]), "+f"(d[12]), "+f"(d[13]), "+f"(d[14]), "+f"(d[15]),
                   "+f"(d[16]), "+f"(d[17]), "+f"(d[18]), "+f"(d[19]), "+f"(d[20]), "+f"(d[21]), "+f"(d[22]), "+f"(d[23]),
                   "+f"(d[24]), "+f"(d[25]), "+f"(d[26]), "+f"(d[27]), "+f"(d[28]), "+f"(d[29]), "+f"(d[30]), "+f"(d[31]),
                   "+f"(d[32]), "+f"(d[33]), "+f"(d[34]), "+f"(d[35]), "+f"(d[36]), "+f"(d[37]), "+f"(d[38]), "+f"(d[39]),
                   "+f"(d[40]), "+f"(d[41]), "+f"(d[42]), "+f"(d[43]), "+f"(d[44]), "+f"(d[45]), "+f"(d[46]), "+f"(d[47]),
                   "+f"(d[48]), "+f"(d[49]), "+f"(d[50]), "+f"(d[51]), "+f"(d[52]), "+f"(d[53]), "+f"(d[54]), "+f"(d[55]),
                   "+f"(d[56]), "+f"(d[57]), "+f"(d[58]), "+f"(d[59]), "+f"(d[60]), "+f"(d[61]), "+f"(d[62]), "+f"(d[63]),
                   "+f"(d[64]), "+f"(d[65]), "+f"(d[66]), "+f"(d[67]), "+f"(d[68]), "+f"(d[69]), "+f"(d[70]), "+f"(d[71]),
                   "+f"(d[72]), "+f"(d[73]), "+f"(d[74]), "+f"(d[75]), "+f"(d[76]), "+f"(d[77]), "+f"(d[78]), "+f"(d[79]),
                   "+f"(d[80]), "+f"(d[81]), "+f"(d[82]), "+f"(d[83]), "+f"(d[84]), "+f"(d[85]), "+f"(d[86]), "+f"(d[87]),
                   "+f"(d[88]), "+f"(d[89]), "+f"(d[90]), "+f"(d[91]), "+f"(d[92]), "+f"(d[93]), "+f"(d[94]), "+f"(d[95])
                 : "l"(da), "l"(db), "r"(scale_d));
}
__device__ __forceinline__ float gelu_tanh(float x) {
    const float u = x * fmaf(x * x, 0.7978845608028654f * 0.044715f, 0.7978845608028654f);
    float th;
    asm("tanh.approx.f32 %0,%1;" : "=f"(th) : "f"(u));
    const float hx = 0.5f * x;
    return fmaf(hx, th, hx);
}
__device__ __forceinline__ float2 ldbf2(const __nv_bfloat16* p) {
    uint32_t w = *reinterpret_cast<const uint32_t*>(p);
    return make_float2(__uint_as_float(w << 16), __uint_as_float(w & 0xffff0000u));
}

__device__ __forceinline__ void bulk_s2g(void* dst, uint32_t src, uint32_t bytes) {
    asm volatile("cp.async.bulk.global.shared::cta.bulk_group [%0],[%1],%2;" ::"l"(dst), "r"(src), "r"(bytes) : "memory");
}
__device__ __forceinline__ uint32_t ld_relaxed1(const void* p) {
    uint32_t v; asm volatile("ld.relaxed.gpu.global.u32 %0,[%1];" : "=r"(v) : "l"(p) : "memory"); return v;
}

__device__ __forceinline__ void tma2d_store(const CUtensorMap* tm, uint32_t src, int c0, int c1) {
    asm volatile("cp.async.bulk.tensor.2d.global.shared::cta.bulk_group [%0,{%2,%3}],[%1];" ::"l"(tm), "r"(src), "r"(c0), "r"(c1) : "memory");
}
__device__ __forceinline__ float4 lds128f(uint32_t a) {
    float4 v; asm volatile("ld.shared.v4.f32 {%0,%1,%2,%3},[%4];" : "=f"(v.x), "=f"(v.y), "=f"(v.z), "=f"(v.w) : "r"(a) : "memory");
    return v;
}
__device__ __forceinline__ float bf_lo(uint32_t w) { return __uint_as_float(w << 16); }
__device__ __forceinline__ float bf_hi(uint32_t w) { return __uint_as_float(w & 0xffff0000u); }

__global__ void __launch_bounds__(384, 1)
k_tail(const __grid_constant__ CUtensorMap tmWo, const __grid_constant__ CUtensorMap tmW1, const __grid_constant__ CUtensorMap tmW2,
       const __grid_constant__ CUtensorMap tmX, const __grid_constant__ CUtensorMap tmOut,
       const __nv_bfloat16* __restrict__ w1, const __nv_bfloat16* __restrict__ b1, const __nv_bfloat16* __restrict__ b2) {
    extern __shared__ uint8_t smem_raw[];
    const uint32_t sb = (smem_u32(smem_raw) + 1023) & ~1023u;
    uint8_t* const smem = smem_raw + (sb - smem_u32(smem_raw));
    const uint32_t bar_full = sb + T_BAR, bar_empty = bar_full + 8 * G_ST, bar_sfull = bar_empty + 8 * G_ST, bar_sempty = bar_sfull + 8;
    volatile int* stage_task = reinterpret_cast<volatile int*>(smem + T_BAR + 128);
    volatile int* store_task = stage_task + 8;
    const int tid = threadIdx.x, lane = tid & 31;
    const int warp = __shfl_sync(~0u, tid >> 5, 0);
    int dead = 0;
    if (tid == 0) {
        for (int i = 0; i < G_ST; i++) { mbar_init(bar_full + 8 * i, 1); mbar_init(bar_empty + 8 * i, 8); }
        mbar_init(bar_sfull, 256); mbar_init(bar_sempty, 1);
        asm volatile("fence.mbarrier_init.release.cluster;" ::: "memory");
    }
    __syncthreads();

    if (warp >= 8) {
      asm volatile("setmaxnreg.dec.sync.aligned.u32 40;");
      if (warp == 8) {
        uint32_t it = 0, nf1 = 0;
        int idle = 0;
        while (true) {
            int task = -1;
            uint4 f = make_uint4(0, 0, 0, 0), cn = make_uint4(99, 99, 99, 99);
            if (lane < 17) { f = ld_relaxed4(g_flag + lane * 16); if (lane < 16) cn = ld_relaxed4(g_flag + lane * 16 + 4); }
            const uint32_t init_done = __shfl_sync(~0u, f.x, 16), init_claimed = __shfl_sync(~0u, f.y, 16);
            const int lrb = lane & 15;
            const bool oW = cn.x < (uint32_t)(3 * ks_w(lrb)), o1 = cn.y < 24u, o2 = cn.z < (uint32_t)(3 * ks_f(lrb));
            const uint32_t m2 = __ballot_sync(~0u, o2 && f.z >= 24u), m1 = __ballot_sync(~0u, o1 && f.y >= 3u), mW = __ballot_sync(~0u, oW && f.x >= 96u);
            const bool open = __any_sync(~0u, oW || o1 || o2);
            int q = -1, rbq = 0;
            if (init_claimed < (uint32_t)NINIT) q = 3;
            else if (init_done >= (uint32_t)NINIT) {
                if (mW) { q = 0; rbq = __ffs(mW) - 1; }
                else if (m1) { q = 1; rbq = __ffs(m1) - 1; }
                else if (m2) { q = 2; rbq = __ffs(m2) - 1; }
            }
            if (q >= 0) {
                if (lane == 0) {
                    const int n = q == 3 ? NINIT : (q == 1 ? 24 : 3 * (q == 2 ? ks_f(rbq) : ks_w(rbq)));
                    uint32_t idx;
                    asm volatile("atom.acquire.gpu.global.add.u32 %0,[%1],1;" : "=r"(idx) : "l"(g_flag + (q == 3 ? FL_CINIT : rbq * 16 + FL_CW + q)) : "memory");
                    if ((int)idx < n) {
                        if (q == 3) task = 3 | (idx << 2);
                        else if (q == 1) task = 1 | (rbq << 2) | (idx << 6);
                        else task = q | (rbq << 2) | ((idx % 3) << 6) | ((idx / 3) << 11);
                    }
                }
                task = __shfl_sync(~0u, task, 0);
                idle = 0;
                if (task < 0) continue;
            } else {
                if (!open || ++idle > (1 << 16)) task = -2;
                else { __nanosleep(100); continue; }
            }
            if (lane == 0) {
                const int type = task & 3, rb = (task >> 2) & 15, nt = (task >> 6) & 31, ks = (task >> 11) & 15;
                if (task < 0 || type == 3) {
                    const int st = it % G_ST;
                    mbar_wait(bar_empty + 8 * st, ((it / G_ST) & 1) ^ 1, dead);
                    stage_task[st] = task;
                    mbar_arrive(bar_full + 8 * st);
                    it++;
                } else {
                    asm volatile("fence.proxy.async;" ::: "memory");
                    int KS, tot;
                    const uint8_t* A;
                    const CUtensorMap* tm;
                    if (type == 0) { KS = ks_w(rb); tot = 64; A = g_ox + (size_t)rb * 64 * 16384; tm = &tmWo; }
                    else if (type == 1) { KS = 1; tot = 9; A = g_hb + (size_t)rb * 9 * 16384; tm = &tmW1; }
                    else { KS = ks_f(rb); tot = 72; A = g_ff + (size_t)rb * 72 * 16384; tm = &tmW2; }
                    const int kp = kpart(tot, KS), k0 = ks * kp, k1 = ks == KS - 1 ? tot : k0 + kp;
                    for (int k = k0; k < k1; k++, it++) {
                        const int st = it % G_ST;
                        mbar_wait(bar_empty + 8 * st, ((it / G_ST) & 1) ^ 1, dead);
                        stage_task[st] = task;
                        const uint32_t a = sb + st * G_STAGE, bb = a + 16384, fb = bar_full + 8 * st;
                        const bool aux = type == 1 && k == 0;
                        mbar_expect_tx(fb, G_STAGE + (aux ? 4608 : 0));
                        bulk_g2s(a, A + (size_t)k * 16384, 16384, fb);
#pragma unroll
                        for (int i = 0; i < 3; i++) tma2d(bb + i * 8192, tm, nt * 192 + i * 64, k * 64, fb);
                        if (aux) {
                            bulk_g2s(sb + T_AUX + (nf1 & 1) * 4608, g_stat + rb * 384, 3072, fb);
                            bulk_g2s(sb + T_AUX + (nf1 & 1) * 4608 + 3072, g_cb + nt * 192, 1536, fb);
                            nf1++;
                        }
                    }
                    if (type != 1 && ks == KS - 1) {
                        const uint8_t* part = reinterpret_cast<const uint8_t*>(g_part + (size_t)(((type >> 1) * 16 + rb) * 3 + nt) * 24 * 256);
                        for (int e = 0; e < 4; e++, it++) {
                            const int st = it % G_ST;
                            mbar_wait(bar_empty + 8 * st, ((it / G_ST) & 1) ^ 1, dead);
                            const uint32_t a = sb + st * G_STAGE, fb = bar_full + 8 * st;
                            mbar_expect_tx(fb, e < 2 ? 32768 : 40960);
                            if (e < 2) {
                                for (int i = 2 * e; i < (e == 0 ? 2 : 3); i++) {
                                    if (type == 0) tma2d(a + (i & 1) * 16384, &tmX, nt * 192 + i * 64, rb * 128, fb);
                                    else bulk_g2s(a + (i & 1) * 16384, g_hb + (size_t)(rb * 9 + nt * 3 + i) * 16384, 16384, fb);
                                }
                            }
                            if (e == 1) {
                                const uint32_t* dn = g_flag + rb * 16 + FL_DONE + (type >> 1) * 3 + nt;
                                int n = 0;
                                while (ld_acquire1(dn) < (uint32_t)(KS - 1)) { if (++n > SPIN_LIMIT) { dead = 1; break; } __nanosleep(40); }
                                asm volatile("fence.proxy.async;" ::: "memory");
                                bulk_g2s(a + 16384, part + 81920, 16384, fb);
                            } else if (e >= 2) bulk_g2s(a, part + (e - 2) * 40960, 40960, fb);
                        }
                    }
                }
            }
            it = __shfl_sync(~0u, it, 0);
            if (task < 0) break;
        }
      } else if (warp == 9) {
        if (lane == 0) {
            uint32_t ph = 0;
            while (true) {
                int n = 0;
                while (!mbar_try(bar_sfull, ph)) { if (++n > (SPIN_LIMIT << 4)) { dead = 1; break; } }
                if (dead) break;
                const int task = *store_task;
                if (task < 0) break;
                const int type = task & 3, rb = (task >> 2) & 15, nt = (task >> 6) & 31, ks = (task >> 11) & 15;
                uint32_t* flag = nullptr;
                bool stored = true;
                if (type == 3) { flag = g_flag + FL_INIT; stored = false; }
                else if (type == 1) { flag = g_flag + rb * 16 + FL_FF; bulk_s2g(g_ff + (size_t)(rb * 72 + nt * 3) * 16384, sb + T_STG, 49152); }
                else if (ks < (type == 0 ? ks_w(rb) : ks_f(rb)) - 1) { flag = g_flag + rb * 16 + FL_DONE + (type >> 1) * 3 + nt; stored = false; }
                else if (type == 0) { flag = g_flag + rb * 16 + FL_H; bulk_s2g(g_hb + (size_t)(rb * 9 + nt * 3) * 16384, sb + T_STG, 49152); }
                else for (int i = 0; i < 3; i++) tma2d_store(&tmOut, sb + T_STG + i * 16384, nt * 192 + i * 64, rb * 128);
                if (stored) {
                    asm volatile("cp.async.bulk.commit_group;\ncp.async.bulk.wait_group.read 0;" ::: "memory");
                    mbar_arrive(bar_sempty);
                    asm volatile("cp.async.bulk.wait_group 0;\nfence.proxy.async;" ::: "memory");
                } else mbar_arrive(bar_sempty);
                if (flag) asm volatile("red.release.gpu.global.add.u32 [%0],1;" ::"l"(flag) : "memory");
                ph ^= 1;
            }
            pdl_wait();
        }
      }
    } else {
        asm volatile("setmaxnreg.inc.sync.aligned.u32 232;");
        const int wg = warp >> 2, g = lane >> 2, t = lane & 3;
        const int lr = wg * 64 + (warp & 3) * 16 + g;
        const uint32_t mrow = (wg * 64 + (warp & 3) * 16 + ((lane >> 3) & 1) * 8 + (lane & 7)) * 128;
        const uint32_t mchk = lane >> 4, mxor = lane & 7;
        for (int i = tid; i < DM; i += 256) reinterpret_cast<float*>(smem + T_B2)[i] = __bfloat162float(b2[i]);
        bar_sync(1, 256);
        uint32_t it = 0, sph = 1, nf1 = 0;
        while (true) {
            {
                int n = 0;
                while (!mbar_try(bar_full + 8 * (it % G_ST), (it / G_ST) & 1)) { if (++n > (SPIN_LIMIT << 4)) { dead = 1; break; } }
            }
            const int task = dead ? -1 : stage_task[it % G_ST];
            if (task < 0) {
                mbar_wait(bar_sempty, sph, dead);
                if (tid == 0) *store_task = -1;
                mbar_arrive(bar_sfull);
                break;
            }
            const int type = task & 3, rb = (task >> 2) & 15, nt = (task >> 6) & 31, ks = (task >> 11) & 15;
            if (type == 3) {
                const int idx = task >> 2;
                __syncwarp();
                if (lane == 0) mbar_arrive(bar_empty + 8 * (it % G_ST));
                it++;
                mbar_wait(bar_sempty, sph, dead); sph ^= 1;
                float a8[8] = {0.f, 0.f, 0.f, 0.f, 0.f, 0.f, 0.f, 0.f};
                const uint4* src = reinterpret_cast<const uint4*>(w1 + idx * 128 + (tid & 15) * 8);
#pragma unroll 12
                for (int k = tid >> 4; k < DM; k += 16) {
                    const uint4 v = src[(size_t)k * (FF / 8)];
                    const uint32_t wv[4] = {v.x, v.y, v.z, v.w};
#pragma unroll
                    for (int j = 0; j < 4; j++) { a8[2 * j] += bf_lo(wv[j]); a8[2 * j + 1] += bf_hi(wv[j]); }
                }
                float* red = reinterpret_cast<float*>(smem + T_STG);
#pragma unroll
                for (int j = 0; j < 8; j++) red[(tid >> 4) * 128 + (tid & 15) * 8 + j] = a8[j];
                bar_sync(1, 256);
                if (tid < 128) {
                    float sum = 0.f;
#pragma unroll
                    for (int j = 0; j < 16; j++) sum += red[j * 128 + tid];
                    g_cb[idx * 128 + tid] = make_float2(sum, __bfloat162float(b1[idx * 128 + tid]));
                }
                for (int u = idx; u < 96; u += NINIT) {
                    const int rbu = (u / 3) & 15;
                    if ((u < 48 ? ks_w(rbu) : ks_f(rbu)) > 2)
                        for (int j = 0; j < 24; j++) g_part[((size_t)u * 24 + j) * 256 + tid] = make_float4(0.f, 0.f, 0.f, 0.f);
                }
                if (tid == 0) *store_task = task;
                mbar_arrive(bar_sfull);
                TLOG_END();
                continue;
            }
            const int KS = type == 0 ? ks_w(rb) : (type == 1 ? 1 : ks_f(rb));
            const int tot = type == 0 ? 64 : (type == 1 ? 9 : 72);
            const int kp = kpart(tot, KS);
            const int nk = ks == KS - 1 ? tot - ks * kp : kp;
            float acc[96];
            for (int k = 0; k < nk; k++, it++) {
                const int st = it % G_ST;
                mbar_wait(bar_full + 8 * st, (it / G_ST) & 1, dead);
                const uint32_t a = sb + st * G_STAGE + wg * 8192, b = sb + st * G_STAGE + 16384;
                const uint64_t da = mk_desc(a, 16, 1024), db = mk_desc(b, 8192, 1024);
                wg_fence();
#pragma unroll
                for (int kk = 0; kk < 4; kk++) wgmma_n192_ss(acc, da + kk * 2, db + kk * 128, (k | kk) != 0);
                wg_commit();
                if (k > 0) {
                    wg_wait<1>();
                    if (lane == 0) mbar_arrive(bar_empty + 8 * ((it - 1) % G_ST));
                }
            }
            wg_wait<0>();
            if (lane == 0) mbar_arrive(bar_empty + 8 * ((it - 1) % G_ST));
            if (ks < KS - 1) {
                float4* part = g_part + (size_t)(((type >> 1) * 16 + rb) * 3 + nt) * 24 * 256 + tid;
                if (KS == 2) {
#pragma unroll
                    for (int j = 0; j < 24; j++) __stcg(part + j * 256, make_float4(acc[4 * j], acc[4 * j + 1], acc[4 * j + 2], acc[4 * j + 3]));
                } else {
#pragma unroll
                    for (int j = 0; j < 24; j++)
                        asm volatile("red.relaxed.gpu.global.add.v4.f32 [%0],{%1,%2,%3,%4};" ::"l"(part + j * 256), "f"(acc[4 * j]), "f"(acc[4 * j + 1]),
                                     "f"(acc[4 * j + 2]), "f"(acc[4 * j + 3]) : "memory");
                }
                mbar_wait(bar_sempty, sph, dead); sph ^= 1;
                if (tid == 0) *store_task = task;
                mbar_arrive(bar_sfull);
                TLOG_END();
                continue;
            }
            uint32_t pk[48];
            if (type != 1) {
#pragma unroll
                for (int e = 0; e < 4; e++, it++) {
                    const int st = it % G_ST;
                    mbar_wait(bar_full + 8 * st, (it / G_ST) & 1, dead);
                    const uint32_t a = sb + st * G_STAGE;
                    if (e < 2) {
#pragma unroll
                        for (int j = e * 16; j < (e == 0 ? 16 : 24); j += 2) {
                            uint32_t rr[4];
                            ldsm4(rr, a + ((j >> 3) & 1) * 16384 + mrow + ((((j & 7) + mchk) ^ mxor) << 4));
                            acc[4 * j] += bf_lo(rr[0]); acc[4 * j + 1] += bf_hi(rr[0]); acc[4 * j + 2] += bf_lo(rr[1]); acc[4 * j + 3] += bf_hi(rr[1]);
                            acc[4 * j + 4] += bf_lo(rr[2]); acc[4 * j + 5] += bf_hi(rr[2]); acc[4 * j + 6] += bf_lo(rr[3]); acc[4 * j + 7] += bf_hi(rr[3]);
                        }
                    }
                    if (e >= 1) {
                        const int j0 = e == 1 ? 20 : (e - 2) * 10, jn = e == 1 ? 4 : 10;
#pragma unroll
                        for (int j = 0; j < jn; j++) {
                            const float4 pv = lds128f(a + (e == 1 ? 16384 : 0) + j * 4096 + tid * 16);
                            acc[4 * (j0 + j)] += pv.x; acc[4 * (j0 + j) + 1] += pv.y; acc[4 * (j0 + j) + 2] += pv.z; acc[4 * (j0 + j) + 3] += pv.w;
                        }
                    }
                    __syncwarp();
                    if (lane == 0) mbar_arrive(bar_empty + 8 * st);
                }
                if (type == 2) {
#pragma unroll
                    for (int j = 0; j < 24; j++) {
                        const float2 bv = lds64f(sb + T_B2 + (nt * 192 + j * 8 + 2 * t) * 4);
                        pk[2 * j] = pack_bf16(acc[4 * j] + bv.x, acc[4 * j + 1] + bv.y);
                        pk[2 * j + 1] = pack_bf16(acc[4 * j + 2] + bv.x, acc[4 * j + 3] + bv.y);
                    }
                } else {
                    float sm0 = 0.f, sm1 = 0.f;
#pragma unroll
                    for (int j = 0; j < 24; j++) {
                        pk[2 * j] = pack_bf16(acc[4 * j], acc[4 * j + 1]);
                        pk[2 * j + 1] = pack_bf16(acc[4 * j + 2], acc[4 * j + 3]);
                        sm0 += bf_lo(pk[2 * j]) + bf_hi(pk[2 * j]);
                        sm1 += bf_lo(pk[2 * j + 1]) + bf_hi(pk[2 * j + 1]);
                    }
                    sm0 += __shfl_xor_sync(~0u, sm0, 1); sm1 += __shfl_xor_sync(~0u, sm1, 1);
                    sm0 += __shfl_xor_sync(~0u, sm0, 2); sm1 += __shfl_xor_sync(~0u, sm1, 2);
                    sm0 *= (1.f / 192.f); sm1 *= (1.f / 192.f);
                    float q0 = 0.f, q1 = 0.f;
#pragma unroll
                    for (int j = 0; j < 24; j++) {
                        float d;
                        d = bf_lo(pk[2 * j]) - sm0; q0 += d * d;
                        d = bf_hi(pk[2 * j]) - sm0; q0 += d * d;
                        d = bf_lo(pk[2 * j + 1]) - sm1; q1 += d * d;
                        d = bf_hi(pk[2 * j + 1]) - sm1; q1 += d * d;
                    }
                    q0 += __shfl_xor_sync(~0u, q0, 1); q1 += __shfl_xor_sync(~0u, q1, 1);
                    q0 += __shfl_xor_sync(~0u, q0, 2); q1 += __shfl_xor_sync(~0u, q1, 2);
                    if (t == 0) {
                        g_stat[(rb * 3 + nt) * 128 + lr] = make_float2(sm0, q0);
                        g_stat[(rb * 3 + nt) * 128 + lr + 8] = make_float2(sm1, q1);
                    }
                }
            } else {
                const uint32_t aux = sb + T_AUX + (nf1 & 1) * 4608;
                nf1++;
                float2 s0[3], s1[3];
#pragma unroll
                for (int i = 0; i < 3; i++) { s0[i] = lds64f(aux + (i * 128 + lr) * 8); s1[i] = lds64f(aux + (i * 128 + lr + 8) * 8); }
                const float mean0 = (s0[0].x + s0[1].x + s0[2].x) * (1.f / 3.f), mean1 = (s1[0].x + s1[1].x + s1[2].x) * (1.f / 3.f);
                float m20 = s0[0].y + s0[1].y + s0[2].y, m21 = s1[0].y + s1[1].y + s1[2].y;
#pragma unroll
                for (int i = 0; i < 3; i++) { m20 += 192.f * (s0[i].x - mean0) * (s0[i].x - mean0); m21 += 192.f * (s1[i].x - mean1) * (s1[i].x - mean1); }
                const float rstd0 = rsqrtf(m20 * (1.f / DM) + 1e-5f), rstd1 = rsqrtf(m21 * (1.f / DM) + 1e-5f);
#pragma unroll
                for (int j = 0; j < 24; j++) {
                    const float4 c4 = lds128f(aux + 3072 + (j * 8 + 2 * t) * 8);
                    pk[2 * j] = pack_bf16(gelu_tanh(fmaf(rstd0, fmaf(-mean0, c4.x, acc[4 * j]), c4.y)),
                                          gelu_tanh(fmaf(rstd0, fmaf(-mean0, c4.z, acc[4 * j + 1]), c4.w)));
                    pk[2 * j + 1] = pack_bf16(gelu_tanh(fmaf(rstd1, fmaf(-mean1, c4.x, acc[4 * j + 2]), c4.y)),
                                              gelu_tanh(fmaf(rstd1, fmaf(-mean1, c4.z, acc[4 * j + 3]), c4.w)));
                }
            }
            mbar_wait(bar_sempty, sph, dead); sph ^= 1;
#pragma unroll
            for (int j = 0; j < 24; j += 2)
                stsm4(sb + T_STG + (j >> 3) * 16384 + mrow + ((((j & 7) + mchk) ^ mxor) << 4), pk[2 * j], pk[2 * j + 1], pk[2 * j + 2], pk[2 * j + 3]);
            fence_async();
            if (tid == 0) *store_task = task;
            mbar_arrive(bar_sfull);
            TLOG_END();
        }
    }
}

typedef CUresult (*EncodeFn)(CUtensorMap*, CUtensorMapDataType, cuuint32_t, void*, const cuuint64_t*, const cuuint64_t*,
                             const cuuint32_t*, const cuuint32_t*, CUtensorMapInterleave, CUtensorMapSwizzle,
                             CUtensorMapL2promotion, CUtensorMapFloatOOBfill);

void make_map(EncodeFn enc, CUtensorMap* tm, const void* ptr, uint64_t inner, uint64_t outer, uint32_t box_inner, uint32_t box_outer) {
    cuuint64_t dims[2] = {inner, outer};
    cuuint64_t strides[1] = {inner * 2};
    cuuint32_t box[2] = {box_inner, box_outer};
    cuuint32_t es[2] = {1, 1};
    enc(tm, CU_TENSOR_MAP_DATA_TYPE_BFLOAT16, 2, const_cast<void*>(ptr), dims, strides, box, es, CU_TENSOR_MAP_INTERLEAVE_NONE,
        CU_TENSOR_MAP_SWIZZLE_128B, CU_TENSOR_MAP_L2_PROMOTION_L2_256B, CU_TENSOR_MAP_FLOAT_OOB_FILL_NONE);
}

}

extern "C" void kernel_launch(void* const* d_in, const int* in_sizes, int n_in, void* d_out, int out_size) {
    const __nv_bfloat16* x = (const __nv_bfloat16*)d_in[0];
    const __nv_bfloat16* mem0 = (const __nv_bfloat16*)d_in[1];
    const __nv_bfloat16* Wq = (const __nv_bfloat16*)d_in[2];
    const __nv_bfloat16* Wk = (const __nv_bfloat16*)d_in[3];
    const __nv_bfloat16* Wv = (const __nv_bfloat16*)d_in[4];
    const __nv_bfloat16* Wo = (const __nv_bfloat16*)d_in[5];
    const __nv_bfloat16* w1 = (const __nv_bfloat16*)d_in[8];
    const __nv_bfloat16* b1 = (const __nv_bfloat16*)d_in[9];
    const __nv_bfloat16* w2 = (const __nv_bfloat16*)d_in[10];
    const __nv_bfloat16* b2 = (const __nv_bfloat16*)d_in[11];
    __nv_bfloat16* out = (__nv_bfloat16*)d_out;
    cudaStream_t stream = cudaStreamPerThread;

    static EncodeFn enc = nullptr;
    if (!enc) {
        cudaDriverEntryPointQueryResult qr;
        void* fn = nullptr;
        cudaGetDriverEntryPoint("cuTensorMapEncodeTiled", &fn, cudaEnableDefault, &qr);
        enc = (EncodeFn)fn;
        cudaFuncSetAttribute(k_chain, cudaFuncAttributeMaxDynamicSharedMemorySize, SM_CHAIN_BYTES);
        cudaFuncSetAttribute(k_tail, cudaFuncAttributeMaxDynamicSharedMemorySize, T_SMEM);
    }
    CUtensorMap tWo, tW1, tW2, tX, tOut;
    make_map(enc, &tX, x, DM, SEQ, 64, 128);
    make_map(enc, &tOut, out, DM, SEQ, 64, 128);
    make_map(enc, &tWo, Wo, DM, HD, 64, 64);
    make_map(enc, &tW1, w1, FF, DM, 64, 64);
    make_map(enc, &tW2, w2, DM, FF, 64, 64);

    k_pre<<<SEQ / 8, 256, 0, stream>>>(x);
    {
        cudaLaunchConfig_t cfg = {};
        cfg.gridDim = dim3(96); cfg.blockDim = dim3(384); cfg.dynamicSmemBytes = SM_CHAIN_BYTES; cfg.stream = stream;
        cudaLaunchAttribute at[1];
        at[0].id = cudaLaunchAttributeProgrammaticStreamSerialization;
        at[0].val.programmaticStreamSerializationAllowed = 1;
        cfg.attrs = at; cfg.numAttrs = 1;
        cudaLaunchKernelEx(&cfg, k_chain, mem0, Wq, Wk, Wv, Wo);
    }
    {
        cudaLaunchConfig_t cfg = {};
        cfg.gridDim = dim3(132); cfg.blockDim = dim3(384); cfg.dynamicSmemBytes = T_SMEM; cfg.stream = stream;
        cudaLaunchAttribute at[1];
        at[0].id = cudaLaunchAttributeProgrammaticStreamSerialization;
        at[0].val.programmaticStreamSerializationAllowed = 1;
        cfg.attrs = at; cfg.numAttrs = 1;
        cudaLaunchKernelEx(&cfg, k_tail, tWo, tW1, tW2, tX, tOut, w1, b1, b2);
    }
}
```

```cpp
#include <cuda_runtime.h>
#include <cuda_bf16.h>
#include <cuda.h>
#include <stdint.h>

namespace {

constexpr int SEQ = 2048, DM = 576, NH = 32, DH = 128, NSEG = 64, FF = 4608, HD = 4096;
constexpr int XN_SEG_BYTES = 32 * DM * 2;
constexpr int SPIN_LIMIT = 1 << 20;

__device__ __align__(1024) uint8_t g_xn[NSEG * XN_SEG_BYTES];
__device__ __align__(1024) uint8_t g_ox[SEQ * HD * 2];
__device__ __align__(1024) uint8_t g_xch[(96 + 3) * 65536];
__device__ uint32_t g_tab[128];
__device__ __align__(1024) uint8_t g_hb[SEQ * DM * 2];
__device__ __align__(1024) uint8_t g_ff[SEQ * FF * 2];
__device__ __align__(1024) float4 g_part[2 * 16 * 3 * 24 * 256];
__device__ __align__(128) float2 g_stat[16 * 3 * 128];
__device__ __align__(128) float2 g_cb[FF];
constexpr int FL_OX = 0, FL_H = 1, FL_FF = 2, FL_CW = 4, FL_C1 = 5, FL_C2 = 6, FL_DONE = 8  , FL_INIT = 256, FL_CINIT = 257, FL_EXIT = 258;
__device__ __align__(128) uint32_t g_flag[17 * 16];
#define TLOG_END()
#define PSTAMP(i)

__device__ __forceinline__ uint32_t smem_u32(const void* p) { return (uint32_t)__cvta_generic_to_shared(p); }
__device__ __forceinline__ uint32_t mapa(uint32_t a, uint32_t r) {
    uint32_t o; asm("mapa.shared::cluster.u32 %0,%1,%2;" : "=r"(o) : "r"(a), "r"(r)); return o;
}
__device__ __forceinline__ void mbar_init(uint32_t bar, uint32_t cnt) {
    asm volatile("mbarrier.init.shared::cta.b64 [%0],%1;" ::"r"(bar), "r"(cnt) : "memory");
}
__device__ __forceinline__ void mbar_expect_tx(uint32_t bar, uint32_t bytes) {
    asm volatile("mbarrier.arrive.expect_tx.shared::cta.b64 _,[%0],%1;" ::"r"(bar), "r"(bytes) : "memory");
}
__device__ __forceinline__ void mbar_arrive(uint32_t bar) {
    asm volatile("mbarrier.arrive.shared::cta.b64 _,[%0];" ::"r"(bar) : "memory");
}
__device__ __forceinline__ bool mbar_try(uint32_t bar, uint32_t ph) {
    uint32_t ok;
    asm volatile("{.reg .pred p; mbarrier.try_wait.parity.shared::cta.b64 p,[%1],%2; selp.u32 %0,1,0,p;}"
                 : "=r"(ok) : "r"(bar), "r"(ph) : "memory");
    return ok;
}
__device__ __forceinline__ bool mbar_try_cluster(uint32_t bar, uint32_t ph) {
    uint32_t ok;
    asm volatile("{.reg .pred p; mbarrier.try_wait.parity.acquire.cluster.shared::cta.b64 p,[%1],%2; selp.u32 %0,1,0,p;}"
                 : "=r"(ok) : "r"(bar), "r"(ph) : "memory");
    return ok;
}
__device__ __forceinline__ void mbar_wait(uint32_t bar, uint32_t ph, int& dead) {
    if (mbar_try(bar, ph)) return;
    int n = dead ? SPIN_LIMIT : 0;
#pragma unroll 1
    while (!mbar_try(bar, ph)) { if (++n > SPIN_LIMIT) { dead = 1; break; } }
}
__device__ __forceinline__ uint32_t opaque(uint32_t v, int lane) { return __shfl_sync(~0u, v, lane); }
__device__ __forceinline__ void mbar_wait_cluster(uint32_t bar, uint32_t ph, int& dead) {
    if (dead) return;
    int n = 0;
    while (!mbar_try_cluster(bar, ph)) { if (++n > SPIN_LIMIT) { dead = 1; break; } }
}
__device__ __forceinline__ void bar_sync(int id, int n) { asm volatile("bar.sync %0,%1;" ::"r"(id), "r"(n) : "memory"); }
__device__ __forceinline__ void bar_arrive(int id, int n) { asm volatile("bar.arrive %0,%1;" ::"r"(id), "r"(n) : "memory"); }
__device__ __forceinline__ void cluster_sync() {
    asm volatile("barrier.cluster.arrive.release.aligned;\nbarrier.cluster.wait.acquire.aligned;" ::: "memory");
}
__device__ __forceinline__ void fence_async() { asm volatile("fence.proxy.async.shared::cta;" ::: "memory"); }

__device__ __forceinline__ void ldsm4(uint32_t (&r)[4], uint32_t a) {
    asm volatile("ldmatrix.sync.aligned.m8n8.x4.shared.b16 {%0,%1,%2,%3},[%4];"
                 : "=r"(r[0]), "=r"(r[1]), "=r"(r[2]), "=r"(r[3]) : "r"(a) : "memory");
}
__device__ __forceinline__ void ldsm4t(uint32_t (&r)[4], uint32_t a) {
    asm volatile("ldmatrix.sync.aligned.m8n8.x4.trans.shared.b16 {%0,%1,%2,%3},[%4];"
                 : "=r"(r[0]), "=r"(r[1]), "=r"(r[2]), "=r"(r[3]) : "r"(a) : "memory");
}
__device__ __forceinline__ void stsm4(uint32_t a, uint32_t r0, uint32_t r1, uint32_t r2, uint32_t r3) {
    asm volatile("stmatrix.sync.aligned.m8n8.x4.shared.b16 [%0],{%1,%2,%3,%4};" ::"r"(a), "r"(r0), "r"(r1), "r"(r2), "r"(r3) : "memory");
}
__device__ __forceinline__ void stsm4t(uint32_t a, uint32_t r0, uint32_t r1, uint32_t r2, uint32_t r3) {
    asm volatile("stmatrix.sync.aligned.m8n8.x4.trans.shared.b16 [%0],{%1,%2,%3,%4};" ::"r"(a), "r"(r0), "r"(r1), "r"(r2), "r"(r3) : "memory");
}
__device__ __forceinline__ void mma16(float (&d)[4], uint32_t a0, uint32_t a1, uint32_t a2, uint32_t a3, uint32_t b0, uint32_t b1) {
    asm volatile("mma.sync.aligned.m16n8k16.row.col.f32.bf16.bf16.f32 {%0,%1,%2,%3},{%4,%5,%6,%7},{%8,%9},{%0,%1,%2,%3};"
                 : "+f"(d[0]), "+f"(d[1]), "+f"(d[2]), "+f"(d[3]) : "r"(a0), "r"(a1), "r"(a2), "r"(a3), "r"(b0), "r"(b1));
}
__device__ __forceinline__ void mma8(float (&d)[4], uint32_t a0, uint32_t a1, uint32_t b0) {
    asm volatile("mma.sync.aligned.m16n8k8.row.col.f32.bf16.bf16.f32 {%0,%1,%2,%3},{%4,%5},{%6},{%0,%1,%2,%3};"
                 : "+f"(d[0]), "+f"(d[1]), "+f"(d[2]), "+f"(d[3]) : "r"(a0), "r"(a1), "r"(b0));
}
__device__ __forceinline__ uint32_t pack_bf16(float lo, float hi) {
    uint32_t r; asm("cvt.rn.bf16x2.f32 %0,%1,%2;" : "=r"(r) : "f"(hi), "f"(lo)); return r;
}
__device__ __forceinline__ float bf_lo(uint32_t w) { return __uint_as_float(w << 16); }
__device__ __forceinline__ float bf_hi(uint32_t w) { return __uint_as_float(w & 0xffff0000u); }
__device__ __forceinline__ float ex2(float x) { float r; asm("ex2.approx.ftz.f32 %0,%1;" : "=f"(r) : "f"(x)); return r; }
__device__ __forceinline__ void st_async32(uint32_t dst, uint32_t v, uint32_t bar) {
    asm volatile("st.async.shared::cluster.mbarrier::complete_tx::bytes.u32 [%0],%1,[%2];" ::"r"(dst), "r"(v), "r"(bar) : "memory");
}
__device__ __forceinline__ void bulk_g2s(uint32_t dst, const void* src, uint32_t bytes, uint32_t bar) {
    asm volatile("cp.async.bulk.shared::cluster.global.mbarrier::complete_tx::bytes [%0],[%1],%2,[%3];"
                 ::"r"(dst), "l"(src), "r"(bytes), "r"(bar) : "memory");
}
__device__ __forceinline__ void bulk_g2s_mc(uint32_t dst, const void* src, uint32_t bytes, uint32_t bar, uint16_t mask) {
    asm volatile("cp.async.bulk.shared::cluster.global.mbarrier::complete_tx::bytes.multicast::cluster [%0],[%1],%2,[%3],%4;"
                 ::"r"(dst), "l"(src), "r"(bytes), "r"(bar), "h"(mask) : "memory");
}
__device__ __forceinline__ void bulk_s2s(uint32_t dst, uint32_t src, uint32_t bytes, uint32_t bar) {
    asm volatile("cp.async.bulk.shared::cluster.shared::cta.mbarrier::complete_tx::bytes [%0],[%1],%2,[%3];"
                 ::"r"(dst), "r"(src), "r"(bytes), "r"(bar) : "memory");
}
__device__ __forceinline__ void tma2d(uint32_t dst, const CUtensorMap* tm, int c0, int c1, uint32_t bar) {
    asm volatile("cp.async.bulk.tensor.2d.shared::cluster.global.mbarrier::complete_tx::bytes [%0],[%1,{%3,%4}],[%2];"
                 ::"r"(dst), "l"(tm), "r"(bar), "r"(c0), "r"(c1) : "memory");
}
__device__ __forceinline__ void cp_async16(uint32_t dst, const void* src) {
    asm volatile("cp.async.cg.shared.global [%0],[%1],16;" ::"r"(dst), "l"(src) : "memory");
}
__device__ __forceinline__ uint4 ld_relaxed4(const void* p) {
    uint4 v;
    asm volatile("ld.relaxed.gpu.global.v4.u32 {%0,%1,%2,%3},[%4];" : "=r"(v.x), "=r"(v.y), "=r"(v.z), "=r"(v.w) : "l"(p) : "memory");
    return v;
}
__device__ __forceinline__ void st_relaxed2(void* p, uint32_t a, uint32_t b) {
    asm volatile("st.relaxed.gpu.global.v2.u32 [%0],{%1,%2};" ::"l"(p), "r"(a), "r"(b) : "memory");
}
__device__ __forceinline__ void st_relaxed1(void* p, uint32_t a) {
    asm volatile("st.relaxed.gpu.global.u32 [%0],%1;" ::"l"(p), "r"(a) : "memory");
}
__device__ __forceinline__ uint32_t ld_relaxed1(const void* p) {
    uint32_t v; asm volatile("ld.relaxed.gpu.global.u32 %0,[%1];" : "=r"(v) : "l"(p) : "memory"); return v;
}
__device__ __forceinline__ void red_add1(uint32_t* p) { asm volatile("red.relaxed.gpu.global.add.u32 [%0],1;" ::"l"(p) : "memory"); }
__device__ __forceinline__ void sts128(uint32_t a, uint4 v) {
    asm volatile("st.shared.v4.u32 [%0],{%1,%2,%3,%4};" ::"r"(a), "r"(v.x), "r"(v.y), "r"(v.z), "r"(v.w) : "memory");
}
__device__ __forceinline__ uint4 lds128(uint32_t a) {
    uint4 v; asm volatile("ld.shared.v4.u32 {%0,%1,%2,%3},[%4];" : "=r"(v.x), "=r"(v.y), "=r"(v.z), "=r"(v.w) : "r"(a) : "memory");
    return v;
}
__device__ __forceinline__ void sts32f(uint32_t a, float v) { asm volatile("st.shared.f32 [%0],%1;" ::"r"(a), "f"(v) : "memory"); }
__device__ __forceinline__ float2 lds64f(uint32_t a) {
    float2 v; asm volatile("ld.shared.v2.f32 {%0,%1},[%2];" : "=f"(v.x), "=f"(v.y) : "r"(a) : "memory"); return v;
}
__device__ __forceinline__ void wg_fence() { asm volatile("wgmma.fence.sync.aligned;" ::: "memory"); }
__device__ __forceinline__ void wg_commit() { asm volatile("wgmma.commit_group.sync.aligned;" ::: "memory"); }
template <int N> __device__ __forceinline__ void wg_wait() { asm volatile("wgmma.wait_group.sync.aligned %0;" ::"n"(N) : "memory"); }
__device__ __forceinline__ uint64_t mk_desc(uint32_t addr, uint32_t lbo, uint32_t sbo) {
    return (uint64_t)((addr & 0x3FFFF) >> 4) | ((uint64_t)(lbo >> 4) << 16) | ((uint64_t)(sbo >> 4) << 32) | (1ull << 62);
}
__device__ __forceinline__ void wgmma_n32_rs(float (&d)[16], const uint32_t (&a)[4], uint64_t desc, int scale_d) {
    asm volatile("{.reg .pred p; setp.ne.b32 p,%21,0;\n"
                 "wgmma.mma_async.sync.aligned.m64n32k16.f32.bf16.bf16 "
                 "{%0,%1,%2,%3,%4,%5,%6,%7,%8,%9,%10,%11,%12,%13,%14,%15},{%16,%17,%18,%19},%20,p,1,1,0;}"
                 : "+f"(d[0]), "+f"(d[1]), "+f"(d[2]), "+f"(d[3]), "+f"(d[4]), "+f"(d[5]), "+f"(d[6]), "+f"(d[7]),
                   "+f"(d[8]), "+f"(d[9]), "+f"(d[10]), "+f"(d[11]), "+f"(d[12]), "+f"(d[13]), "+f"(d[14]), "+f"(d[15])
                 : "r"(a[0]), "r"(a[1]), "r"(a[2]), "r"(a[3]), "l"(desc), "r"(scale_d));
}
__device__ __forceinline__ void wgmma_n32_rs_tb(float (&d)[16], const uint32_t (&a)[4], uint64_t desc) {
    asm volatile("wgmma.mma_async.sync.aligned.m64n32k16.f32.bf16.bf16 "
                 "{%0,%1,%2,%3,%4,%5,%6,%7,%8,%9,%10,%11,%12,%13,%14,%15},{%16,%17,%18,%19},%20,1,1,1,1;"
                 : "+f"(d[0]), "+f"(d[1]), "+f"(d[2]), "+f"(d[3]), "+f"(d[4]), "+f"(d[5]), "+f"(d[6]), "+f"(d[7]),
                   "+f"(d[8]), "+f"(d[9]), "+f"(d[10]), "+f"(d[11]), "+f"(d[12]), "+f"(d[13]), "+f"(d[14]), "+f"(d[15])
                 : "r"(a[0]), "r"(a[1]), "r"(a[2]), "r"(a[3]), "l"(desc));
}
__device__ __forceinline__ void wgmma_n8_rs(float (&d)[4], uint32_t a0, uint32_t a1, uint32_t a2, uint32_t a3, uint64_t desc) {
    asm volatile("wgmma.mma_async.sync.aligned.m64n8k16.f32.bf16.bf16 {%0,%1,%2,%3},{%4,%5,%6,%7},%8,1,1,1,0;"
                 : "+f"(d[0]), "+f"(d[1]), "+f"(d[2]), "+f"(d[3]) : "r"(a0), "r"(a1), "r"(a2), "r"(a3), "l"(desc));
}
__device__ __forceinline__ void wgmma_n32_ss_tb0(float (&d)[16], uint64_t da, uint64_t desc) {
    asm volatile("wgmma.mma_async.sync.aligned.m64n32k16.f32.bf16.bf16 "
                 "{%0,%1,%2,%3,%4,%5,%6,%7,%8,%9,%10,%11,%12,%13,%14,%15},%16,%17,0,1,1,0,1;"
                 : "=f"(d[0]), "=f"(d[1]), "=f"(d[2]), "=f"(d[3]), "=f"(d[4]), "=f"(d[5]), "=f"(d[6]), "=f"(d[7]),
                   "=f"(d[8]), "=f"(d[9]), "=f"(d[10]), "=f"(d[11]), "=f"(d[12]), "=f"(d[13]), "=f"(d[14]), "=f"(d[15])
                 : "l"(da), "l"(desc));
}
__device__ __forceinline__ void wgmma_n32_ss(float (&d)[16], uint64_t da, uint64_t desc) {
    asm volatile("wgmma.mma_async.sync.aligned.m64n32k16.f32.bf16.bf16 "
                 "{%0,%1,%2,%3,%4,%5,%6,%7,%8,%9,%10,%11,%12,%13,%14,%15},%16,%17,1,1,1,0,0;"
                 : "+f"(d[0]), "+f"(d[1]), "+f"(d[2]), "+f"(d[3]), "+f"(d[4]), "+f"(d[5]), "+f"(d[6]), "+f"(d[7]),
                   "+f"(d[8]), "+f"(d[9]), "+f"(d[10]), "+f"(d[11]), "+f"(d[12]), "+f"(d[13]), "+f"(d[14]), "+f"(d[15])
                 : "l"(da), "l"(desc));
}
__device__ __forceinline__ void pdl_wait() { asm volatile("griddepcontrol.wait;" ::: "memory"); }
__device__ __forceinline__ void pdl_launch() { asm volatile("griddepcontrol.launch_dependents;" ::: "memory"); }

__device__ __forceinline__ void ln_load(uint4 (&v)[3], const __nv_bfloat16* __restrict__ x, int row, int lane) {
    const uint4* src = reinterpret_cast<const uint4*>(x + (size_t)row * DM);
#pragma unroll
    for (int i = 0; i < 3; i++) {
        v[i] = make_uint4(0, 0, 0, 0);
        if (lane + 32 * i < 72 && row < SEQ)
            asm volatile("ld.global.nc.v4.u32 {%0,%1,%2,%3},[%4];" : "=r"(v[i].x), "=r"(v[i].y), "=r"(v[i].z), "=r"(v[i].w) : "l"(src + lane + 32 * i));
    }
}
__device__ __forceinline__ void ln_row(const uint4 (&v)[3], int row, int lane) {
    float f[24];
    float sum = 0.f;
#pragma unroll
    for (int i = 0; i < 3; i++) {
        const uint32_t w[4] = {v[i].x, v[i].y, v[i].z, v[i].w};
#pragma unroll
        for (int j = 0; j < 4; j++) {
            f[i * 8 + 2 * j] = __uint_as_float(w[j] << 16);
            f[i * 8 + 2 * j + 1] = __uint_as_float(w[j] & 0xffff0000u);
            sum += f[i * 8 + 2 * j] + f[i * 8 + 2 * j + 1];
        }
    }
#pragma unroll
    for (int o = 16; o; o >>= 1) sum += __shfl_xor_sync(~0u, sum, o);
    const float mean = sum * (1.f / DM);
    float var = 0.f;
#pragma unroll
    for (int i = 0; i < 3; i++) {
        if (lane + 32 * i < 72) {
#pragma unroll
            for (int j = 0; j < 8; j++) { float d = f[i * 8 + j] - mean; var += d * d; }
        }
    }
#pragma unroll
    for (int o = 16; o; o >>= 1) var += __shfl_xor_sync(~0u, var, o);
    const float rstd = rsqrtf(var * (1.f / DM) + 1e-5f);
    const int seg = row >> 5, r = row & 31;
#pragma unroll
    for (int i = 0; i < 3; i++) {
        const int c = lane + 32 * i;
        if (c < 72) {
            uint4 o;
            o.x = pack_bf16((f[i * 8 + 0] - mean) * rstd, (f[i * 8 + 1] - mean) * rstd);
            o.y = pack_bf16((f[i * 8 + 2] - mean) * rstd, (f[i * 8 + 3] - mean) * rstd);
            o.z = pack_bf16((f[i * 8 + 4] - mean) * rstd, (f[i * 8 + 5] - mean) * rstd);
            o.w = pack_bf16((f[i * 8 + 6] - mean) * rstd, (f[i * 8 + 7] - mean) * rstd);
            *reinterpret_cast<uint4*>(g_xn + (size_t)seg * XN_SEG_BYTES + (c >> 3) * 4096 + r * 128 + (((c & 7) ^ (r & 7)) << 4)) = o;
        }
    }
}

constexpr int SM_XN = 0;
constexpr int SM_X = 73728;
constexpr int SM_MB = SM_X + 3 * 24576;
constexpr int SXR = 56;
constexpr int SMR = 80;
constexpr int SM_SX = SM_MB + 3 * 6144;
constexpr int SM_SXX = SM_SX + 8 * SMR * 4;
constexpr int SM_OT = SM_SXX + 16 * SXR * 4;
constexpr int SM_OX = SM_OT + 2048;
constexpr int SM_MAIN_END = SM_OX + 4096;
constexpr int SM_STG_W = XN_SEG_BYTES;
constexpr int SM_MEMT = SM_STG_W + 147456;
#define NREGK 33
constexpr int NREG_K = NREGK;
constexpr int SM_WS = SM_MEMT + 9216;
constexpr int SM_TAB = SM_WS + (36 - NREG_K) * 4096;
constexpr int SM_AUX = SM_TAB + 4096;
constexpr int SM_BAR = SM_AUX + 12288;
constexpr int SM_TIM = SM_BAR + 128;
constexpr int SM_CHAIN_BYTES = SM_TIM + 1024;
static_assert(SM_MAIN_END <= SM_MEMT && SM_TAB % 1024 == 0 && SM_STG_W % 1024 == 0, "smem");
static_assert(SM_CHAIN_BYTES <= 232448, "smem");
constexpr int BAR_MEM = 1, BAR_GO = 2, BAR_A = 3, BAR_B = 4, BAR_QD = 5, BAR_GO2 = 6, BAR_S = 7, BAR_U = 8;
#define BULK1 22

__device__ __forceinline__ uint32_t clk32() { uint32_t t; asm volatile("mov.u32 %0,%%clock;" : "=r"(t)::"memory"); return t; }
#define TSTAMP(i)
#define TFLUSH()
#define PIN(x) asm volatile("" : "+r"(x))
#define PINL(x) asm volatile("" : "+l"(x))

__device__ __forceinline__ uint2 ld_relaxed2(const void* p) {
    uint2 v;
    asm volatile("ld.relaxed.gpu.global.v2.u32 {%0,%1},[%2];" : "=r"(v.x), "=r"(v.y) : "l"(p) : "memory");
    return v;
}
__device__ __forceinline__ uint32_t ld_acquire1(const void* p) {
    uint32_t v; asm volatile("ld.acquire.gpu.global.u32 %0,[%1];" : "=r"(v) : "l"(p) : "memory"); return v;
}
__device__ __forceinline__ uint32_t xand(uint32_t a, uint32_t b, uint32_t m) {
    uint32_t r; asm("lop3.b32 %0,%1,%2,%3,0x42;" : "=r"(r) : "r"(a), "r"(b), "r"(m)); return r;
}
__device__ __forceinline__ uint32_t and3(uint32_t a, uint32_t b, uint32_t c) {
    uint32_t r; asm("lop3.b32 %0,%1,%2,%3,0x80;" : "=r"(r) : "r"(a), "r"(b), "r"(c)); return r;
}
__device__ __forceinline__ uint32_t settag(float v, uint32_t tag) {
    uint32_t r; asm("lop3.b32 %0,%1,0xfffffffe,%2,0xea;" : "=r"(r) : "r"(__float_as_uint(v)), "r"(tag)); return r;
}
__device__ __forceinline__ float rcp_fast(float x) { float r; asm("rcp.approx.ftz.f32 %0,%1;" : "=f"(r) : "f"(x)); return r; }
__device__ __forceinline__ void sts64f(uint32_t a, float x, float y) { asm volatile("st.shared.v2.f32 [%0],{%1,%2};" ::"r"(a), "f"(x), "f"(y) : "memory"); }

__device__ __forceinline__ uint32_t near_parity(uint8_t* blk, int cta) {
    uint32_t best[2] = {~0u, ~0u};
    for (int r = 0; r < 3; r++)
#pragma unroll
        for (int p = 0; p < 2; p++) {
            uint8_t* a = blk + (0xF000 ^ (p << 12)) + (cta & 31) * 128;
            uint32_t v, t1 = 0;
            const uint32_t t0 = clk32();
            asm volatile("atom.relaxed.gpu.global.add.u32 %0,[%1],1;" : "=r"(v) : "l"(a) : "memory");
            asm volatile("{.reg .pred p; setp.ne.u32 p,%1,0x7fffffff; @p mov.u32 %0,%%clock;}" : "+r"(t1) : "r"(v) : "memory");
            best[p] = min(best[p], t1 - t0);
        }
    return best[0] <= best[1] ? 0u : 1u;
}

template <int GRP>
__device__ __forceinline__ void xfinish(uint32_t sxa, uint32_t vaa, uint32_t vma, uint32_t st_w, uint32_t st_r, uint8_t* dst, int g, int t, int nbar) {
    constexpr int NB = GRP + 2;
    constexpr bool needB = (GRP >= 2);
    const float sc = 0.08838834764831845f * 1.4426950408889634f;
    bar_sync(BAR_A, nbar);
    float2 v[6];
#pragma unroll
    for (int b = 0; b < NB + 1; b++) v[b] = lds64f(sxa + b * 32);
    uint32_t f0[4], f1[4];
    ldsm4(f0, vma);
    v[1].x += v[0].x; v[1].y += v[0].y;
    if (2 * t > g) v[NB].x = -INFINITY;
    if (2 * t + 1 > g) v[NB].y = -INFINITY;
    float mx = fmaxf(v[1].x, v[1].y);
#pragma unroll
    for (int b = 2; b < NB + 1; b++) mx = fmaxf(mx, fmaxf(v[b].x, v[b].y));
    mx = fmaxf(mx, __shfl_xor_sync(~0u, mx, 1));
    mx = fmaxf(mx, __shfl_xor_sync(~0u, mx, 2));
    mx *= sc;
    uint32_t pk[5];
    float sum = 0.f;
#pragma unroll
    for (int b = 0; b < 5; b++) {
        if (b < NB) {
            float p0 = ex2(fmaf(v[b + 1].x, sc, -mx)), p1 = ex2(fmaf(v[b + 1].y, sc, -mx));
            sum += p0 + p1;
            pk[b] = pack_bf16(p0, p1);
        } else pk[b] = 0u;
    }
    float o[2][4] = {{0.f, 0.f, 0.f, 0.f}, {0.f, 0.f, 0.f, 0.f}};
    ldsm4(f1, vaa);
    mma8(o[0], f0[0], f0[1], pk[0]);
    mma8(o[1], f0[2], f0[3], pk[0]);
    ldsm4(f0, vaa + 256);
    sum += __shfl_xor_sync(~0u, sum, 1);
    mma16(o[0], f1[0], f1[1], f1[2], f1[3], pk[1], pk[2]);
    if (needB) ldsm4(f1, vaa + 4096);
    mma16(o[1], f0[0], f0[1], f0[2], f0[3], pk[1], pk[2]);
    if (needB) ldsm4(f0, vaa + 4096 + 256);
    sum += __shfl_xor_sync(~0u, sum, 2);
    if (needB) {
        mma16(o[0], f1[0], f1[1], f1[2], f1[3], pk[3], pk[4]);
        mma16(o[1], f0[0], f0[1], f0[2], f0[3], pk[3], pk[4]);
    }
    const float s0 = __shfl_sync(~0u, sum, 8 * t), s1 = __shfl_sync(~0u, sum, 8 * t + 4);
    const float i0 = rcp_fast(s0), i1 = rcp_fast(s1);
    stsm4t(st_w, pack_bf16(o[0][0] * i0, o[0][1] * i1), pack_bf16(o[0][2] * i0, o[0][3] * i1),
           pack_bf16(o[1][0] * i0, o[1][1] * i1), pack_bf16(o[1][2] * i0, o[1][3] * i1));
    __syncwarp();
    uint4 val = lds128(st_r);
    *reinterpret_cast<uint4*>(dst + GRP * 1024) = val;
}

__device__ __forceinline__ void xrest(uint32_t sb, uint32_t xs, uint32_t mb, int c, int h, int s, int w, int lane, int wg) {
    const int g = lane >> 2, t = lane & 3, m = lane >> 3, r = lane & 7;
    const uint32_t sxa = sb + SM_SXX + (g * SXR + 2 * t) * 4;
    const uint32_t vaa = xs + 16384 + (m >> 1) * 2048 + (32 * w + 8 * (m & 1) + r) * 16;
    const uint32_t vma = mb + 4096 + (32 * w + lane) * 16;
    const uint32_t st_w = sb + SM_OX + w * 512 + r * 64 + ((m ^ ((r >> 1) & 3)) << 4);
    const uint32_t st_r = sb + SM_OX + w * 512 + g * 64 + ((t ^ ((g >> 1) & 3)) << 4);
    uint8_t* dst = g_ox + (size_t)((s >> 2) * 64 + 2 * h + (w >> 1)) * 16384 + ((s & 3) * 32 + g) * 128 + ((((w & 1) * 4 + t) ^ g) << 4);
    if (wg == 0) xfinish<0>(sxa, vaa, vma, st_w + 2048, st_r + 2048, dst, g, t, 256);
    else if (c == 2) xfinish<1>(sxa + 8 * SXR * 4, vaa, vma, st_w, st_r, dst, g, t, 256);
    else if (c == 0) xfinish<3>(sxa + 8 * SXR * 4, vaa, vma, st_w, st_r, dst, g, t, 128);
    else xfinish<2>(sxa, vaa, vma, st_w, st_r, dst, g, t, 128);
}

__device__ __forceinline__ void xattn(uint32_t sb, uint32_t xs, uint32_t mb, uint32_t barq, uint32_t phq, int c, int h, int s, int w, int lane, int& dead) {
    const int g = lane >> 2, t = lane & 3, m = lane >> 3, r = lane & 7;
    if (w < 2) {
        const int kt = (c == 2) ? 0 : w, grp = (c == 2) ? w : 3 - c;
        const uint32_t kb = xs + 8192 + (2 * kt + (m & 1)) * 2048 + (8 * (m >> 1) + r) * 16;
        const uint32_t qb = xs + grp * 2048 + lane * 16;
        float c0[4] = {0.f, 0.f, 0.f, 0.f}, c1[4] = {0.f, 0.f, 0.f, 0.f};
#pragma unroll
        for (int j = 0; j < 4; j++) {
            uint32_t q[4], a[4], b[4];
            ldsm4t(q, qb + j * 512);
            ldsm4t(a, kb + j * 512);
            ldsm4t(b, kb + j * 512 + 256);
            mma16(c0, a[0], a[1], a[2], a[3], q[0], q[1]);
            mma16(c1, b[0], b[1], b[2], b[3], q[2], q[3]);
        }
        const uint32_t p = sb + SM_SXX + (((grp & 1) * 8 + 2 * t) * SXR + 16 + 16 * kt + g) * 4;
        sts32f(p, c0[0] + c1[0]);
        sts32f(p + SXR * 4, c0[1] + c1[1]);
        sts32f(p + 32, c0[2] + c1[2]);
        sts32f(p + SXR * 4 + 32, c0[3] + c1[3]);
        mbar_wait(barq, phq, dead);
    } else {
        const uint4 at = lds128(sb + SM_AUX + (128 + w * 32 + lane) * 16);
        const uint32_t qa = mb + at.y, ka = mb + at.w, sxw = at.z;
        mbar_wait(barq, phq, dead);
        uint32_t a[2][4];
        {
            uint32_t q[2][4];
            float c0[4] = {0.f, 0.f, 0.f, 0.f}, c1[4] = {0.f, 0.f, 0.f, 0.f};
            ldsm4t(q[0], qa); ldsm4t(a[0], ka); ldsm4t(q[1], qa + 512); ldsm4t(a[1], ka + 512);
            mma16(c0, a[0][0], a[0][1], a[0][2], a[0][3], q[0][0], q[0][1]);
            mma16(c1, a[0][0], a[0][1], a[0][2], a[0][3], q[0][2], q[0][3]);
            mma16(c0, a[1][0], a[1][1], a[1][2], a[1][3], q[1][0], q[1][1]);
            mma16(c1, a[1][0], a[1][1], a[1][2], a[1][3], q[1][2], q[1][3]);
            sts32f(sxw, c0[0] + c1[2]);
            sts32f(sxw + SMR * 4, c0[1] + c1[3]);
            if (s < NSEG - 1) bar_arrive(BAR_S, 320);
        }
        uint32_t qx[4][4];
        const uint32_t base = xs + ((c == 2 ? 0 : 2) + (m & 1)) * 2048 + ((w - 2) * 64 + 8 * (m >> 1) + r) * 16;
#pragma unroll
        for (int j = 0; j < 4; j++) ldsm4t(qx[j], base + j * 256);
        float c2[4] = {0.f, 0.f, 0.f, 0.f}, c3[4] = {0.f, 0.f, 0.f, 0.f};
#pragma unroll
        for (int j = 0; j < 2; j++) {
            mma16(c2, qx[2 * j][0], qx[2 * j][1], qx[2 * j][2], qx[2 * j][3], a[j][0], a[j][1]);
            mma16(c3, qx[2 * j + 1][0], qx[2 * j + 1][1], qx[2 * j + 1][2], qx[2 * j + 1][3], a[j][2], a[j][3]);
        }
        const uint32_t sxx = sb + SM_SXX + (g * SXR + 8 * (w - 2) + 2 * t) * 4;
        sts64f(sxx, c2[0] + c3[0], c2[1] + c3[1]);
        sts64f(sxx + 8 * SXR * 4, c2[2] + c3[2], c2[3] + c3[3]);
    }
    xrest(sb, xs, mb, c, h, s, w, lane, 1);
}

#define PAUSE_BOTH 0
#define VLATE 0
#define FENCE_EARLY 1
#define REGS_A 176
#define POLL_MODE 0
#define UMID 2
#define DELAY1 380
#define STAG1 200
#define DELAY2 280
#define STAG2 200
#define DELAY2N 1000

__device__ __forceinline__ void st_relaxed64(void* p, uint32_t lo, uint32_t hi) {
    asm volatile("{.reg .b64 v; mov.b64 v,{%1,%2}; st.relaxed.gpu.global.b64 [%0],v;}" ::"l"(p), "r"(lo), "r"(hi) : "memory");
}
__device__ __forceinline__ uint2 ld_relaxed64(const void* p) {
    uint2 v;
    asm volatile("{.reg .b64 v; ld.relaxed.gpu.global.b64 v,[%2]; mov.b64 {%0,%1},v;}" : "=r"(v.x), "=r"(v.y) : "l"(p) : "memory");
    return v;
}
__device__ __forceinline__ void sts32(uint32_t a, uint32_t v) { asm volatile("st.shared.u32 [%0],%1;" ::"r"(a), "r"(v) : "memory"); }

__global__ void __cluster_dims__(3, 1, 1) __launch_bounds__(384, 1)
k_chain(const __grid_constant__ CUtensorMap tmWq, const __grid_constant__ CUtensorMap tmWk, const __grid_constant__ CUtensorMap tmWv,
        const __grid_constant__ CUtensorMap tmWo, const __nv_bfloat16* __restrict__ x, const __nv_bfloat16* __restrict__ mem0,
        uint8_t* __restrict__ xb) {
    extern __shared__ __align__(1024) uint8_t smem[];
    const uint32_t sb = smem_u32(smem);
    const int tid = threadIdx.x, lane = tid & 31;
    const int warp = __shfl_sync(~0u, tid >> 5, 0);
    const int c = blockIdx.x % 3, h = blockIdx.x / 3;
    const uint32_t bar_qm = sb + SM_BAR, bar_x = sb + SM_BAR + 24, bar_xn = sb + SM_BAR + 48, bar_xf = sb + SM_BAR + 64, bar_w = sb + SM_BAR + 72;
    int dead = 0;

    pdl_launch();
    {
        if (tid == 0) {
            for (int i = 0; i < 11; i++) mbar_init(bar_qm + 8 * i, i < 3 ? 9 : (i == 8 ? 24 : 1));
            asm volatile("fence.mbarrier_init.release.cluster;" ::: "memory");
        }
        const int r0 = warp == 11 ? blockIdx.x : 96 + blockIdx.x * 11 + warp, r1 = warp == 11 ? SEQ : r0 + 1056;
        uint4 xr0[3], xr1[3];
        ln_load(xr0, x, r0, lane);
        ln_load(xr1, x, r1, lane);
        uint4 m0[5];
#pragma unroll
        for (int i = 0; i < 5; i++) {
            m0[i] = make_uint4(0, 0, 0, 0);
            if (warp >= 8 && tid - 256 + i * 128 < 576)
                asm volatile("ld.global.nc.v4.u32 {%0,%1,%2,%3},[%4];" : "=r"(m0[i].x), "=r"(m0[i].y), "=r"(m0[i].z), "=r"(m0[i].w)
                             : "l"(reinterpret_cast<const uint4*>(mem0) + tid - 256 + i * 128));
        }
        __syncthreads();
        if (warp == 8) PSTAMP(14);
        if (tid == 0) {
            asm volatile("{.reg .pred p; setp.eq.u32 p,%0,0x7fc1a5a5; @p nanosleep.u32 1;}" ::"r"(xr0[0].x ^ xr1[1].y) : "memory");
            mbar_expect_tx(bar_w + 8, 49152);
            for (int i = 0; i < 6; i++)
                tma2d(sb + (i < 4 ? SM_XN + i * 8192 : SM_TAB + (i - 4) * 8192), &tmWo, c * 192 + (i >> 1) * 64, h * DH + (i & 1) * 64, bar_w + 8);
            const CUtensorMap* tw = c == 0 ? &tmWq : (c == 1 ? &tmWk : &tmWv);
            mbar_expect_tx(bar_w, 147456);
            for (int i = 0; i < 6; i++) tma2d(sb + SM_STG_W + (i & 1) * 73728 + (i >> 1) * 24576, tw, h * DH + (i & 1) * 64, (i >> 1) * 192, bar_w);
        }
        ln_row(xr0, r0, lane);
        if (warp == 11) {
            asm volatile("fence.acq_rel.gpu;" ::: "memory");
            __syncwarp();
            if (lane == 0) red_add1(g_tab + 100);
        }
        if (warp >= 8) {
#pragma unroll
            for (int i = 0; i < 5; i++) {
                const int ci = tid - 256 + i * 128;
                if (ci < 576) {
                    const uint32_t wv[4] = {m0[i].x, m0[i].y, m0[i].z, m0[i].w};
                    uint16_t* dst = reinterpret_cast<uint16_t*>(smem + SM_MEMT + (ci % 72) * 128 + (ci / 72) * 2);
#pragma unroll
                    for (int j = 0; j < 4; j++) { dst[16 * j] = (uint16_t)wv[j]; dst[16 * j + 8] = (uint16_t)(wv[j] >> 16); }
                }
            }
        }
        if (warp == 8) PSTAMP(15);
        if (r1 < SEQ) ln_row(xr1, r1, lane);
        if (warp < 8) {
            uint8_t* blk = xb + (size_t)blockIdx.x * 65536;
            uint8_t* c2b = xb + (size_t)96 * 65536;
            for (int i = tid; i < 1024; i += 256) *reinterpret_cast<uint4*>(blk + (i >> 9) * 32768 + (i & 511) * 16) = make_uint4(0, 0, 0, 0);
            if (tid < 48) {
                const int o = blockIdx.x * 96 + (tid % 6) * 16, v = tid / 6;
                *reinterpret_cast<uint4*>(c2b + (v >> 2) * 65536 + (v & 3) * 4096 + (o >> 12) * 16384 + (o & 4095)) = make_uint4(0, 0, 0, 0);
            } else if (tid < 60) {
                const int v = tid - 48;
                *reinterpret_cast<uint4*>((v < 4 ? blk : c2b + ((v >> 2) - 1) * 65536) + 0xE000 + ((v >> 1) & 1) * 4096 + (blockIdx.x & 31) * 128 + (v & 1) * 16) = make_uint4(0, 0, 0, 0);
            }
            bar_arrive(BAR_QD, 384);
        }
        PSTAMP(4);
    }
    auto ship_x = [&](int sl) {
        const uint32_t src = sb + SM_X + sl * 24576 + c * 8192, bx = bar_x + sl * 8;
        const uint32_t p1 = (c + 1) % 3, p2 = (c + 2) % 3;
        bulk_s2s(mapa(src, p1), src, 8192, mapa(bx, p1));
        bulk_s2s(mapa(src, p2), src, 8192, mapa(bx, p2));
        mbar_expect_tx(bx, 16384);
    };
    auto load_xn = [&](int seg) {
        const int b = seg & 1;
        mbar_expect_tx(bar_xn + 8 * b, XN_SEG_BYTES);
        bulk_g2s_mc(sb + SM_XN + b * XN_SEG_BYTES + c * 12288, g_xn + (size_t)seg * XN_SEG_BYTES + c * 12288, 12288, bar_xn + 8 * b, 7);
    };

    if (warp < 8) {
        if (REGS_A > 168) asm volatile("setmaxnreg.inc.sync.aligned.u32 %0;" ::"n"(REGS_A));
        mbar_wait(bar_w, 0, dead);
        PSTAMP(10);
        uint32_t W[NREG_K][4];
        {
            const int m = lane >> 3, r = lane & 7;
            const uint32_t wa = sb + SM_STG_W + (warp >> 2) * 73728 + (8 * (m >> 1) + r) * 128 + (((2 * (warp & 3) + (m & 1)) ^ r) << 4);
#pragma unroll
            for (int j = 0; j < 36; j++) {
                if (j < NREG_K) ldsm4t(W[j], wa + j * 2048);
                else {
                    uint32_t f[4];
                    ldsm4t(f, wa + j * 2048);
                    stsm4(sb + SM_WS + (j - NREG_K) * 4096 + (m >> 1) * 2048 + (2 * warp + (m & 1)) * 128 + r * 16, f[0], f[1], f[2], f[3]);
                }
            }
            fence_async();
        }
        bar_sync(BAR_A, 256);
        if (tid == 0) {
            int n = 0;
            while (ld_acquire1(g_tab + 100) < 96u) { if (++n > SPIN_LIMIT) { dead = 1; break; } }
            asm volatile("fence.proxy.async;" ::: "memory");
            mbar_expect_tx(bar_xn + 8, XN_SEG_BYTES);
            bulk_g2s(sb + SM_XN + XN_SEG_BYTES, g_xn + XN_SEG_BYTES, XN_SEG_BYTES, bar_xn + 8);
        }
        __syncwarp();
        asm volatile("barrier.cluster.arrive.relaxed.aligned;" ::: "memory");
        const uint32_t rb1 = mapa(sb, (c + 1) % 3), rb2 = mapa(sb, (c + 2) % 3);
        int slot = 0, ph3 = 0;
        for (int s = -2; s < NSEG; s++) {
            const int sl = slot == 2 ? 0 : slot + 1;
            int lane;
            asm volatile("mov.u32 %0,%%laneid;" : "=r"(lane));
            if (s >= 0) {
                uint32_t WS[36 - NREG_K][4];
                {
                    const uint32_t a = sb + SM_WS + ((lane >> 4) & 1) * 2048 + (2 * warp + ((lane >> 3) & 1)) * 128 + (lane & 7) * 16;
#pragma unroll
                    for (int j = 0; j < 36 - NREG_K; j++) ldsm4(WS[j], a + j * 4096);
                }
                const uint32_t doff = SM_MB + c * 2048 + warp * 256 + lane * 4 + sl * 6144;
                const uint32_t ma = sb + SM_MEMT + lane * 16;
                bar_sync(BAR_MEM, 384);
                float a0[4] = {0.f, 0.f, 0.f, 0.f}, a1[4] = {0.f, 0.f, 0.f, 0.f}, a2[4] = {0.f, 0.f, 0.f, 0.f};
                uint32_t b[5][4];
                constexpr int J0 = NREG_K / 2;
                ldsm4t(b[0], ma + J0 * 512);
                ldsm4t(b[1], ma + ((J0 + 1) % 18) * 512);
                TSTAMP(0);
#pragma unroll
                for (int jj = 0; jj < 18; jj++) {
                    const int j = (jj + J0) % 18;
                    if (jj == 1) { ldsm4t(b[2], ma + ((J0 + 2) % 18) * 512); ldsm4t(b[3], ma + ((J0 + 3) % 18) * 512); }
                    if (jj >= 1 && jj + 3 < 18) ldsm4t(b[(jj + 3) % 5], ma + ((jj + 3 + J0) % 18) * 512);
                    const uint32_t(&bb)[4] = b[jj % 5];
                    float(&c0)[4] = (2 * jj) % 3 == 0 ? a0 : ((2 * jj) % 3 == 1 ? a1 : a2);
                    float(&c1)[4] = (2 * jj + 1) % 3 == 0 ? a0 : ((2 * jj + 1) % 3 == 1 ? a1 : a2);
                    if (2 * j < NREG_K) mma16(c0, W[2 * j][0], W[2 * j][1], W[2 * j][2], W[2 * j][3], bb[0], bb[1]);
                    else mma16(c0, WS[2 * j - NREG_K][0], WS[2 * j - NREG_K][1], WS[2 * j - NREG_K][2], WS[2 * j - NREG_K][3], bb[0], bb[1]);
                    if (2 * j + 1 < NREG_K) mma16(c1, W[2 * j + 1][0], W[2 * j + 1][1], W[2 * j + 1][2], W[2 * j + 1][3], bb[2], bb[3]);
                    else mma16(c1, WS[2 * j + 1 - NREG_K][0], WS[2 * j + 1 - NREG_K][1], WS[2 * j + 1 - NREG_K][2], WS[2 * j + 1 - NREG_K][3], bb[2], bb[3]);
                }
                const uint32_t w0 = pack_bf16(a0[0] + a1[0] + a2[0], a0[1] + a1[1] + a2[1]);
                const uint32_t w1 = pack_bf16(a0[2] + a1[2] + a2[2], a0[3] + a1[3] + a2[3]);
                const uint32_t boff = SM_BAR + sl * 8;
                st_async32(rb1 + doff, w0, rb1 + boff); st_async32(rb2 + doff, w0, rb2 + boff);
                st_async32(rb1 + doff + 128, w1, rb1 + boff); st_async32(rb2 + doff + 128, w1, rb2 + boff);
                sts32(sb + doff, w0); sts32(sb + doff + 128, w1);
                __syncwarp();
                if (lane == 0) mbar_arrive(sb + boff);
                if (!FENCE_EARLY) fence_async();
                if (s < NSEG - 1) bar_arrive(BAR_U, 384);
                TSTAMP(1);
            }
            const int sn = s + 2;
            const bool bulk = sn < NSEG;
            const uint64_t desc0 = mk_desc(sb + SM_XN + (sn & 1) * XN_SEG_BYTES, 16, 1024);
            const uint64_t da = (uint64_t)(((sb + SM_WS + (warp >> 2) * 1024) & 0x3FFFF) >> 4) | (128ull << 16) | (8ull << 32);
            float acc[16];
            if (s >= 0) {
                mbar_wait(bar_x + sl * 8, ph3, dead);
                const uint32_t xs = sb + SM_X + sl * 24576, mb = sb + SM_MB + sl * 6144;
                if (warp < 4) {
                    if (s == NSEG - 1) {
                        if (c == 2) xrest(sb, xs, mb, c, h, s, warp, lane, 0);
                        bar_arrive(BAR_GO, 256);
                        break;
                    }
                    const uint4 at = lds128(sb + SM_AUX + (warp * 32 + lane) * 16);
                    const uint32_t qa = mb + at.y, sxw = at.z;
                    uint32_t kf[4][4];
#pragma unroll
                    for (int j = 0; j < 4; j++) ldsm4t(kf[j], xs + at.w + j * 256);
                    mbar_wait(bar_qm + sl * 8, ph3, dead);
                    uint32_t q[2][4];
                    ldsm4t(q[0], qa); ldsm4t(q[1], qa + 512);
                    float c0[4] = {0.f, 0.f, 0.f, 0.f}, c1[4] = {0.f, 0.f, 0.f, 0.f}, c2[4] = {0.f, 0.f, 0.f, 0.f}, c3[4] = {0.f, 0.f, 0.f, 0.f};
                    mma16(c0, kf[0][0], kf[0][1], kf[0][2], kf[0][3], q[0][0], q[0][1]);
                    mma16(c1, kf[1][0], kf[1][1], kf[1][2], kf[1][3], q[0][2], q[0][3]);
                    mma16(c2, kf[2][0], kf[2][1], kf[2][2], kf[2][3], q[1][0], q[1][1]);
                    mma16(c3, kf[3][0], kf[3][1], kf[3][2], kf[3][3], q[1][2], q[1][3]);
                    sts32f(sxw, (c0[0] + c1[0]) + (c2[0] + c3[0]));
                    sts32f(sxw + SMR * 4, (c0[1] + c1[1]) + (c2[1] + c3[1]));
                    sts32f(sxw + 64, (c0[2] + c1[2]) + (c2[2] + c3[2]));
                    sts32f(sxw + SMR * 4 + 64, (c0[3] + c1[3]) + (c2[3] + c3[3]));
                    bar_arrive(BAR_S, 320);
                    TSTAMP(2);
                    __syncwarp();
                    if (c == 2) xrest(sb, xs, mb, c, h, s, warp, lane, 0);
                    TSTAMP(5);
                    bar_sync(BAR_GO, 256);
                } else {
                    xattn(sb, xs, mb, bar_qm + sl * 8, ph3, c, h, s, warp - 4, lane, dead);
                    TSTAMP(2);
                    if (s == NSEG - 1) {
                        bar_sync(BAR_GO, 256);
                        if (tid == 128) { asm volatile("fence.acq_rel.gpu;" ::: "memory"); red_add1(g_flag + 15 * 16 + FL_OX); }
                        break;
                    }
                    bar_sync(BAR_GO2, 256);
                }
            }
#pragma unroll
            for (int i = 0; i < 16; i++) acc[i] = 0.f;
            if (bulk) {
                mbar_wait(bar_xn + (sn & 1) * 8, (sn >> 1) & 1, dead);
                wg_fence();
#pragma unroll
                for (int j = 0; j < BULK1; j++) wgmma_n32_rs(acc, W[j], desc0 + (uint64_t)(((j >> 2) * 4096 + (j & 3) * 32) >> 4), j > 0);
                wg_commit();
                wg_wait<0>();
            }
            if (s >= 0) bar_sync(BAR_QD, 320);
            if (bulk) {
                wg_fence();
#pragma unroll
                for (int j = BULK1; j < NREG_K; j++) wgmma_n32_rs(acc, W[j], desc0 + (uint64_t)(((j >> 2) * 4096 + (j & 3) * 32) >> 4), j > 0);
#pragma unroll
                for (int j = NREG_K; j < 36; j++)
                    wgmma_n32_ss(acc, da + (uint64_t)((j - NREG_K) * 256), desc0 + (uint64_t)(((j >> 2) * 4096 + (j & 3) * 32) >> 4));
                wg_commit();
                wg_wait<0>();
            }
            if (s > -2 && lane < 3)
                asm volatile("mbarrier.arrive.relaxed.cluster.shared::cluster.b64 _,[%0];" ::"r"(mapa(bar_xf, lane)) : "memory");
            TSTAMP(3);
            if (bulk) {
                const uint32_t xo = sb + SM_X + slot * 24576 + c * 8192 + ((lane >> 4) & 1) * 2048 + (16 * warp + 8 * ((lane >> 3) & 1) + (lane & 7)) * 16;
                stsm4(xo, pack_bf16(acc[0], acc[1]), pack_bf16(acc[2], acc[3]), pack_bf16(acc[4], acc[5]), pack_bf16(acc[6], acc[7]));
                stsm4(xo + 4096, pack_bf16(acc[8], acc[9]), pack_bf16(acc[10], acc[11]), pack_bf16(acc[12], acc[13]), pack_bf16(acc[14], acc[15]));
                if (FENCE_EARLY || s == -2) fence_async();
            }
            if (s == -2) {
                asm volatile("barrier.cluster.wait.acquire.aligned;" ::: "memory");
                bar_arrive(0, 288);
            }
            TSTAMP(4);
            if (s >= 0) { TFLUSH(); }
            if (sl == 2 && s >= 0) ph3 ^= 1;
            slot = sl;
        }
        cluster_sync();
    } else {
        if (REGS_A > 168) asm volatile("setmaxnreg.dec.sync.aligned.u32 %0;" ::"n"(504 - 2 * REGS_A));
        const int w = warp - 8, bt = tid - 256;
        const int cta = blockIdx.x;
        uint8_t* const c2b = xb + (size_t)96 * 65536;
        PSTAMP(11);
        asm volatile("barrier.cluster.arrive.relaxed.aligned;" ::: "memory");
        PSTAMP(12);
        PSTAMP(13);
        mbar_wait(bar_w + 8, 0, dead);
        PSTAMP(6);
        uint32_t WO[3][8][4];
        {
            const int m = lane >> 3, r = lane & 7;
#pragma unroll
            for (int i = 0; i < 3; i++)
#pragma unroll
                for (int j = 0; j < 8; j++) {
                    const int k = 16 * j + 8 * (m >> 1) + r, ch = 2 * (3 * w + i) + (m & 1);
                    ldsm4t(WO[i][j], sb + (ch < 16 ? SM_XN + (ch >> 3) * 16384 : SM_TAB) + k * 128 + (((ch & 7) ^ r) << 4));
                }
        }
        bar_sync(BAR_QD, 384);
        {
            const int g = lane >> 2, t = lane & 3, m = lane >> 3, r = lane & 7;
            sts128(sb + SM_AUX + bt * 16, make_uint4(0, (w & 1) * 1024 + lane * 16,
                   sb + SM_SX + (2 * t * SMR + (1 + (w & 2)) * 16 + (g >> 1) * 4 + (w & 1) * 2 + (g & 1)) * 4,
                   8192 + ((w & 2) + (m & 1)) * 2048 + ((w & 1) * 64 + 8 * (m >> 1) + r) * 16));
            sts128(sb + SM_AUX + 2048 + bt * 16, make_uint4(0, (w & 1) * 1024 + ((((m & 1) << 1) | (m >> 1)) * 8 + r) * 16,
                   sb + SM_SX + (2 * t * SMR + (g >> 1) * 4 + (w & 1) * 2 + (g & 1)) * 4, 2048 + (w & 1) * 1024 + lane * 16));
        }
        bar_arrive(BAR_MEM, 384);
        volatile uint32_t* sp = reinterpret_cast<volatile uint32_t*>(smem + SM_TIM + 900);
        if (lane == 0) {
            if (w == 0) {
                int n = 0;
                while (ld_acquire1(g_tab + 100) < 96u) { if (++n > SPIN_LIMIT) { dead = 1; break; } }
                asm volatile("fence.proxy.async;" ::: "memory");
                mbar_expect_tx(bar_xn, XN_SEG_BYTES);
                bulk_g2s(sb + SM_XN, g_xn, XN_SEG_BYTES, bar_xn);
            } else {
                const uint32_t pr = near_parity(w == 1 ? xb + (size_t)cta * 65536 : c2b + (w - 2) * 65536, cta);
                sp[w] = pr;
                if (w == 1) {
                    asm volatile("fence.acq_rel.gpu;" ::: "memory");
                    st_relaxed1(g_tab + cta, 1u + pr);
                }
            }
        }
        __syncwarp();
        PSTAMP(7);
        asm volatile("barrier.cluster.wait.acquire.aligned;" ::: "memory");
        if (w == 0) {
            bar_sync(0, 288);
            PSTAMP(9);
            if (lane == 0) {
                asm volatile("fence.proxy.async;" ::: "memory");
                ship_x(0);
                mbar_wait(bar_x, 0, dead);
                load_xn(2);
            }
        } else {
            uint32_t tv;
            int n = 0;
            while ((tv = ld_acquire1(g_tab + bt - 32)) == 0u) { if (++n > SPIN_LIMIT) { dead = 1; break; } }
            reinterpret_cast<volatile uint8_t*>(smem + SM_TIM + 800)[bt - 32] = (uint8_t)(tv - 1);
        }
        dead = __any_sync(~0u, dead);
        bar_sync(BAR_B, 128);
        const uint32_t pinfo = __shfl_sync(~0u, sp[2] | (sp[3] << 1) | (sp[1] << 2), 0);
        if (bt == 0) asm volatile("fence.proxy.async;" ::: "memory");
        PSTAMP(5);
        for (int i = 0; i < 3; i++) {
            const int u = (c * 12 + w * 3 + i) * 4 + (lane >> 3), d = u < 96 ? u : 2 * (u - 96);
            reinterpret_cast<volatile uint32_t*>(smem + SM_TAB)[bt * 4 + i] =
                d * 65536 + (reinterpret_cast<volatile uint8_t*>(smem + SM_TIM + 800)[d] & 1) * 4096 + (u < 96 ? 0 : 2048) + h * 64 + (lane & 7) * 8;
        }
        reinterpret_cast<volatile uint32_t*>(smem + SM_TAB)[bt * 4 + 3] = sb + SM_SX + ((lane >> 2) * SMR + 4 * (lane & 3)) * 4;
        PSTAMP(8);
        __syncwarp();
        const float sc = 0.08838834764831845f * 1.4426950408889634f;
        int slot = 0, ph3 = 0;
        for (int s = 0; s < NSEG; s++) {
            int lane;
            asm volatile("mov.u32 %0,%%laneid;" : "=r"(lane));
            const int g = lane >> 2, t = lane & 3, m = lane >> 3, r = lane & 7, bt = w * 32 + lane;
            const uint32_t xs = sb + SM_X + slot * 24576;
            const uint32_t mb = sb + SM_MB + slot * 6144;
            if (bt == 64) mbar_expect_tx(bar_qm + slot * 8, 4096);
            if (s == NSEG - 1) break;
            const uint32_t tag = ((s >> 1) & 1) ^ 1;
            const uint4 tab = lds128(sb + SM_TAB + bt * 16);
            const uint32_t sxr = tab.w;
            const uint32_t l16 = sb + lane * 16;
            const uint32_t one = 0x3f803f80u;
            uint32_t va[2][2][4], vmm[4];
            mbar_wait(bar_x + slot * 8, ph3, dead);
            bar_sync(BAR_U, 384);
            if (bt == 32 && s + 3 < NSEG) {
                mbar_wait(bar_xf, s & 1, dead);
                load_xn(s + 3);
            }
            __syncwarp();
            const uint32_t vaa = xs + 16384 + (m >> 1) * 2048 + (32 * w + 8 * (m & 1) + r) * 16;
            ldsm4(va[0][0], vaa); ldsm4(va[1][0], vaa + 256);
            ldsm4(va[0][1], vaa + 4096); ldsm4(va[1][1], vaa + 4096 + 256);
            TSTAMP(1);
            mbar_wait(bar_qm + slot * 8, ph3, dead);
            ldsm4(vmm, mb + 4096 + bt * 16);
            if (bt == 64) {
                ship_x(slot == 2 ? 0 : slot + 1);
            }
            __syncwarp();
            TSTAMP(2);
            bar_sync(BAR_S, 320);
            float2 v[5];
            {
                uint4 u[5];
#pragma unroll
                for (int b = 0; b < 5; b++) u[b] = lds128(sxr + b * 64);
#pragma unroll
                for (int b = 0; b < 5; b++) v[b] = make_float2(__uint_as_float(u[b].x) + __uint_as_float(u[b].z), __uint_as_float(u[b].y) + __uint_as_float(u[b].w));
            }
            TSTAMP(3);
            float mx = fmaxf(fmaxf(fmaxf(v[4].x, v[4].y), fmaxf(v[1].x, v[1].y)), fmaxf(fmaxf(v[2].x, v[2].y), fmaxf(v[3].x, v[3].y)));
            mx = fmaxf(mx, fmaxf(v[0].x, v[0].y));
            mx = fmaxf(mx, __shfl_xor_sync(~0u, mx, 1));
            mx = fmaxf(mx, __shfl_xor_sync(~0u, mx, 2));
            mx *= sc;
            float o[2][4] = {{0.f, 0.f, 0.f, 0.f}, {0.f, 0.f, 0.f, 0.f}}, rs[4] = {0.f, 0.f, 0.f, 0.f};
            {
                uint32_t pk[5];
#pragma unroll
                for (int b = 0; b < 5; b++) pk[b] = pack_bf16(ex2(fmaf(v[b].x, sc, -mx)), ex2(fmaf(v[b].y, sc, -mx)));
                mma8(o[0], vmm[0], vmm[1], pk[0]);
                mma8(o[1], vmm[2], vmm[3], pk[0]);
                mma8(rs, one, one, pk[0]);
                mma16(o[0], va[0][0][0], va[0][0][1], va[0][0][2], va[0][0][3], pk[1], pk[2]);
                mma16(o[1], va[1][0][0], va[1][0][1], va[1][0][2], va[1][0][3], pk[1], pk[2]);
                mma16(rs, one, one, one, one, pk[1], pk[2]);
                mma16(o[0], va[0][1][0], va[0][1][1], va[0][1][2], va[0][1][3], pk[3], pk[4]);
                mma16(o[1], va[1][1][0], va[1][1][1], va[1][1][2], va[1][1][3], pk[3], pk[4]);
                mma16(rs, one, one, one, one, pk[3], pk[4]);
                stsm4(l16 + SM_OT + w * 512, pack_bf16(o[0][0], o[0][1]), pack_bf16(o[0][2], o[0][3]), pack_bf16(o[1][0], o[1][1]), pack_bf16(o[1][2], o[1][3]));
                TSTAMP(4);
                bar_sync(BAR_B, 128);
            }
            uint32_t ob[4][4];
#pragma unroll
            for (int j = 0; j < 4; j++) ldsm4t(ob[j], l16 + SM_OT + j * 512);
            TSTAMP(5);
            {
                float d[3][2][4];
#pragma unroll
                for (int i = 0; i < 3; i++)
#pragma unroll
                    for (int k = 0; k < 4; k++) d[i][0][k] = d[i][1][k] = 0.f;
#pragma unroll
                for (int j = 0; j < 8; j++)
#pragma unroll
                    for (int i = 0; i < 3; i++)
                        mma16(d[i][j & 1], WO[i][j][0], WO[i][j][1], WO[i][j][2], WO[i][j][3], ob[j >> 1][(j & 1) * 2], ob[j >> 1][(j & 1) * 2 + 1]);
                const float i0 = rcp_fast(rs[0]), i1 = rcp_fast(rs[1]);
                uint8_t* const xs1 = xb + (s & 1) * 32768;
                const uint32_t off[3] = {tab.x, tab.y, tab.z};
#pragma unroll
                for (int i = 0; i < 3; i++)
                    st_relaxed64(xs1 + off[i], settag(__uint_as_float(pack_bf16((d[i][0][0] + d[i][1][0]) * i0, (d[i][0][1] + d[i][1][1]) * i1)), tag),
                                 pack_bf16((d[i][0][2] + d[i][1][2]) * i0, (d[i][0][3] + d[i][1][3]) * i1));
            }
            const uint32_t t_st = clk32();
            TSTAMP(6);
            const bool owner = w == 0 || (w == 1 && !(cta & 1));
            const uint8_t* src = xb + (cta * 65536 + (pinfo & 4u) * 1024 + (s & 1) * 32768 + (w & 1) * 2048) + (uint32_t)(t * 64 + g * 8);
            bar_arrive(BAR_GO, 256);
            bar_arrive(BAR_GO2, 256);
            const uint8_t* src2 = c2b + (((s >> 1) & 1) * 65536 + ((s & 1) * 0x3000 ^ (((pinfo >> ((s >> 1) & 1)) & 1) << 12))) + (uint32_t)(bt * 16);
            const uint32_t mt = sb + SM_MEMT + bt * 16;
            uint32_t t_pub = 0;
            if (owner) {
                const int u = w == 0 ? cta : 96 + (cta >> 1), o = (u >> 2) * 256 + (u & 3) * 32;
                const uint32_t o_pub = (o >> 12) * 16384 + (o & 4095) + (t & 1) * 128 + g * 4 + (t >> 1) * 0x1000;
                const uint32_t msk = tag ^ 1u;
                int n = 0;
                uint2 v2[8];
                while ((int)(clk32() - t_st) < DELAY1);
#pragma unroll
                for (int i = 0; i < 8; i++) v2[i] = ld_relaxed64(src + i * 256);
                TSTAMP(7);
                const uint32_t sel = (g & 1) ? 0x3f800000u : 0x00003f80u;
                uint8_t* const pub = c2b + (((s >> 1) & 1) * 65536 + (s & 1) * 0x2000) + o_pub;
                while (!__all_sync(~0u, (and3(xand(v2[0].x, v2[1].x, msk), xand(v2[2].x, v2[3].x, msk), xand(v2[4].x, v2[5].x, msk) & xand(v2[6].x, v2[7].x, msk)) | dead) & 1u)) {
#pragma unroll
                    for (int i = 0; i < 8; i++) if (!((v2[i].x ^ msk) & 1u)) v2[i] = ld_relaxed64(src + i * 256);
                    if (++n > SPIN_LIMIT) dead = 1;
                }
                float r0[4] = {0.f, 0.f, 0.f, 0.f}, r1[4] = {0.f, 0.f, 0.f, 0.f}, r2[4] = {0.f, 0.f, 0.f, 0.f}, r3[4] = {0.f, 0.f, 0.f, 0.f};
                mma16(r0, v2[0].x, v2[0].y, v2[1].x, v2[1].y, sel, sel);
                mma16(r1, v2[2].x, v2[2].y, v2[3].x, v2[3].y, sel, sel);
                mma16(r2, v2[4].x, v2[4].y, v2[5].x, v2[5].y, sel, sel);
                mma16(r3, v2[6].x, v2[6].y, v2[7].x, v2[7].y, sel, sel);
                uint32_t word = (t & 1) ? pack_bf16((r0[2] + r1[2]) + (r2[2] + r3[2]), (r0[3] + r1[3]) + (r2[3] + r3[3]))
                                        : pack_bf16((r0[0] + r1[0]) + (r2[0] + r3[0]), (r0[1] + r1[1]) + (r2[1] + r3[1]));
                if (word == 0u) word = 0x80000000u;
                st_relaxed1(pub, word);
                t_pub = clk32();
                st_relaxed1(c2b + ((((s - 1) >> 1) & 1) * 65536 + ((s - 1) & 1) * 0x2000) + o_pub, 0u);
            }
            if (w < 2) bar_arrive(BAR_QD, 320);
            {
                bar_sync(BAR_B, 128);
                asm volatile("{.reg .pred p; .reg .u32 x; ld.shared.u32 x,[%1]; setp.ne.u32 p,x,0x7fc1a5a5; @p mov.u32 %0,%%clock;}" : "+r"(t_pub) : "r"(sb + SM_TAB) : "memory");
            }
            TSTAMP(8);
            {
                uint4 v4[5];
                uint32_t ok[5];
                v4[4] = make_uint4(1, 1, 1, 1);
                while ((int)(clk32() - t_pub) < DELAY2);
#pragma unroll
                for (int i = 0; i < 4; i++) v4[i] = ld_relaxed4(src2 + (i & 1) * 2048 + (i >> 1) * 16384);
                if (w >= 2) v4[4] = ld_relaxed4(src2 + 32768 - 1024);
                int n = 0;
                while (true) {
#pragma unroll
                    for (int i = 0; i < 4; i++) sts128(mt + i * 2048, v4[i]);
                    if (w >= 2) sts128(mt + 8192 - 1024, v4[4]);
#pragma unroll
                    for (int i = 0; i < 5; i++) ok[i] = min(__vimin3_u32(v4[i].x, v4[i].y, v4[i].z), v4[i].w);
                    const uint32_t all = min(__vimin3_u32(ok[0], ok[1], ok[2]), min(ok[3], ok[4]));
                    if (__all_sync(~0u, (all | dead) != 0)) break;
#pragma unroll
                    for (int i = 0; i < 5; i++) if (!ok[i]) v4[i] = ld_relaxed4(src2 + (i & 1) * 2048 + (i >> 1) * 16384 - (i == 4 ? 1024 : 0));
                    if (++n > SPIN_LIMIT) dead = 1;
                }
                bar_arrive(BAR_MEM, 384);
            }
            TSTAMP(9);
            if (w == 3 && (s & 3) == 0 && s > 0) {
                asm volatile("fence.acq_rel.gpu;" ::: "memory");
                if (lane == 0) red_add1(g_flag + ((s >> 2) - 1) * 16 + FL_OX);
            }
            TSTAMP(10);
            TFLUSH();
            if (slot == 2) { slot = 0; ph3 ^= 1; } else slot++;
        }
        if (bt == 0) { g_tab[cta] = 0u; if (cta == 0) g_tab[100] = 0u; }
        cluster_sync();
    }
}

constexpr int G_ST = 4;
constexpr int G_STAGE = 16384 + 24576;
constexpr int T_STG = G_ST * G_STAGE;
constexpr int T_AUX = T_STG + 49152;
constexpr int T_B2 = T_AUX + 2 * 4608;
constexpr int T_BAR = T_B2 + 2304;
constexpr int T_SMEM = T_BAR + 256 + 1024;
constexpr int NINIT = 36;
__host__ __device__ constexpr int ks_w(int rb) { return rb == 0 ? 8 : (rb < 12 ? 2 : (rb < 15 ? 4 : 12)); }
__host__ __device__ constexpr int ks_f(int rb) { return rb < 8 ? 2 : (rb < 14 ? 4 : (rb < 15 ? 8 : 11)); }
__host__ __device__ constexpr int kpart(int total, int ks) { return ks == 2 ? total / 2 - 4 : (ks == 4 ? total / 4 - 2 : (ks == 8 ? total / 8 - 1 : total / ks)); }

__device__ __forceinline__ void wgmma_n192_ss(float (&d)[96], uint64_t da, uint64_t db, int scale_d) {
    asm volatile("{.reg .pred p; setp.ne.b32 p,%98,0;\n"
                 "wgmma.mma_async.sync.aligned.m64n192k16.f32.bf16.bf16 {"
                 "%0,%1,%2,%3,%4,%5,%6,%7,%8,%9,%10,%11,%12,%13,%14,%15,%16,%17,%18,%19,%20,%21,%22,%23,"
                 "%24,%25,%26,%27,%28,%29,%30,%31,%32,%33,%34,%35,%36,%37,%38,%39,%40,%41,%42,%43,%44,%45,%46,%47,"
                 "%48,%49,%50,%51,%52,%53,%54,%55,%56,%57,%58,%59,%60,%61,%62,%63,%64,%65,%66,%67,%68,%69,%70,%71,"
                 "%72,%73,%74,%75,%76,%77,%78,%79,%80,%81,%82,%83,%84,%85,%86,%87,%88,%89,%90,%91,%92,%93,%94,%95},"
                 "%96,%97,p,1,1,0,1;}"
                 : "+f"(d[0]), "+f"(d[1]), "+f"(d[2]), "+f"(d[3]), "+f"(d[4]), "+f"(d[5]), "+f"(d[6]), "+f"(d[7]),
                   "+f"(d[8]), "+f"(d[9]), "+f"(d[10]), "+f"(d[11]), "+f"(d[12]), "+f"(d[13]), "+f"(d[14]), "+f"(d[15]),
                   "+f"(d[16]), "+f"(d[17]), "+f"(d[18]), "+f"(d[19]), "+f"(d[20]), "+f"(d[21]), "+f"(d[22]), "+f"(d[23]),
                   "+f"(d[24]), "+f"(d[25]), "+f"(d[26]), "+f"(d[27]), "+f"(d[28]), "+f"(d[29]), "+f"(d[30]), "+f"(d[31]),
                   "+f"(d[32]), "+f"(d[33]), "+f"(d[34]), "+f"(d[35]), "+f"(d[36]), "+f"(d[37]), "+f"(d[38]), "+f"(d[39]),
                   "+f"(d[40]), "+f"(d[41]), "+f"(d[42]), "+f"(d[43]), "+f"(d[44]), "+f"(d[45]), "+f"(d[46]), "+f"(d[47]),
                   "+f"(d[48]), "+f"(d[49]), "+f"(d[50]), "+f"(d[51]), "+f"(d[52]), "+f"(d[53]), "+f"(d[54]), "+f"(d[55]),
                   "+f"(d[56]), "+f"(d[57]), "+f"(d[58]), "+f"(d[59]), "+f"(d[60]), "+f"(d[61]), "+f"(d[62]), "+f"(d[63]),
                   "+f"(d[64]), "+f"(d[65]), "+f"(d[66]), "+f"(d[67]), "+f"(d[68]), "+f"(d[69]), "+f"(d[70]), "+f"(d[71]),
                   "+f"(d[72]), "+f"(d[73]), "+f"(d[74]), "+f"(d[75]), "+f"(d[76]), "+f"(d[77]), "+f"(d[78]), "+f"(d[79]),
                   "+f"(d[80]), "+f"(d[81]), "+f"(d[82]), "+f"(d[83]), "+f"(d[84]), "+f"(d[85]), "+f"(d[86]), "+f"(d[87]),
                   "+f"(d[88]), "+f"(d[89]), "+f"(d[90]), "+f"(d[91]), "+f"(d[92]), "+f"(d[93]), "+f"(d[94]), "+f"(d[95])
                 : "l"(da), "l"(db), "r"(scale_d));
}
__device__ __forceinline__ float gelu_tanh(float x) {
    const float u = x * fmaf(x * x, 0.7978845608028654f * 0.044715f, 0.7978845608028654f);
    float th;
    asm("tanh.approx.f32 %0,%1;" : "=f"(th) : "f"(u));
    const float hx = 0.5f * x;
    return fmaf(hx, th, hx);
}
__device__ __forceinline__ float2 ldbf2(const __nv_bfloat16* p) {
    uint32_t w = *reinterpret_cast<const uint32_t*>(p);
    return make_float2(__uint_as_float(w << 16), __uint_as_float(w & 0xffff0000u));
}

__device__ __forceinline__ void bulk_s2g(void* dst, uint32_t src, uint32_t bytes) {
    asm volatile("cp.async.bulk.global.shared::cta.bulk_group [%0],[%1],%2;" ::"l"(dst), "r"(src), "r"(bytes) : "memory");
}

__device__ __forceinline__ void tma2d_store(const CUtensorMap* tm, uint32_t src, int c0, int c1) {
    asm volatile("cp.async.bulk.tensor.2d.global.shared::cta.bulk_group [%0,{%2,%3}],[%1];" ::"l"(tm), "r"(src), "r"(c0), "r"(c1) : "memory");
}
__device__ __forceinline__ float4 lds128f(uint32_t a) {
    float4 v; asm volatile("ld.shared.v4.f32 {%0,%1,%2,%3},[%4];" : "=f"(v.x), "=f"(v.y), "=f"(v.z), "=f"(v.w) : "r"(a) : "memory");
    return v;
}

__global__ void __launch_bounds__(384, 1)
k_tail(const __grid_constant__ CUtensorMap tmWo, const __grid_constant__ CUtensorMap tmW1, const __grid_constant__ CUtensorMap tmW2,
       const __grid_constant__ CUtensorMap tmX, const __grid_constant__ CUtensorMap tmOut,
       const __nv_bfloat16* __restrict__ w1, const __nv_bfloat16* __restrict__ b1, const __nv_bfloat16* __restrict__ b2) {
    extern __shared__ uint8_t smem_raw[];
    const uint32_t sb = (smem_u32(smem_raw) + 1023) & ~1023u;
    uint8_t* const smem = smem_raw + (sb - smem_u32(smem_raw));
    const uint32_t bar_full = sb + T_BAR, bar_empty = bar_full + 8 * G_ST, bar_sfull = bar_empty + 8 * G_ST, bar_sempty = bar_sfull + 8;
    volatile int* stage_task = reinterpret_cast<volatile int*>(smem + T_BAR + 128);
    volatile int* store_task = stage_task + 8;
    const int tid = threadIdx.x, lane = tid & 31;
    const int warp = __shfl_sync(~0u, tid >> 5, 0);
    int dead = 0;
    if (tid == 0) {
        for (int i = 0; i < G_ST; i++) { mbar_init(bar_full + 8 * i, 1); mbar_init(bar_empty + 8 * i, 8); }
        mbar_init(bar_sfull, 256); mbar_init(bar_sempty, 1);
        asm volatile("fence.mbarrier_init.release.cluster;" ::: "memory");
    }
    __syncthreads();

    if (warp >= 8) {
      asm volatile("setmaxnreg.dec.sync.aligned.u32 40;");
      if (warp == 8) {
        uint32_t it = 0, nf1 = 0;
        int idle = 0;
        while (true) {
            int task = -1;
            uint4 f = make_uint4(0, 0, 0, 0), cn = make_uint4(99, 99, 99, 99);
            if (lane < 17) { f = ld_relaxed4(g_flag + lane * 16); if (lane < 16) cn = ld_relaxed4(g_flag + lane * 16 + 4); }
            const uint32_t init_done = __shfl_sync(~0u, f.x, 16), init_claimed = __shfl_sync(~0u, f.y, 16);
            const int lrb = lane & 15;
            const bool oW = cn.x < (uint32_t)(3 * ks_w(lrb)), o1 = cn.y < 24u, o2 = cn.z < (uint32_t)(3 * ks_f(lrb));
            const uint32_t m2 = __ballot_sync(~0u, o2 && f.z >= 24u), m1 = __ballot_sync(~0u, o1 && f.y >= 3u), mW = __ballot_sync(~0u, oW && f.x >= 96u);
            const bool open = __any_sync(~0u, oW || o1 || o2);
            int q = -1, rbq = 0;
            if (init_claimed < (uint32_t)NINIT) q = 3;
            else if (init_done >= (uint32_t)NINIT) {
                if (mW) { q = 0; rbq = __ffs(mW) - 1; }
                else if (m1) { q = 1; rbq = __ffs(m1) - 1; }
                else if (m2) { q = 2; rbq = __ffs(m2) - 1; }
            }
            if (q >= 0) {
                if (lane == 0) {
                    const int n = q == 3 ? NINIT : (q == 1 ? 24 : 3 * (q == 2 ? ks_f(rbq) : ks_w(rbq)));
                    uint32_t idx;
                    asm volatile("atom.acquire.gpu.global.add.u32 %0,[%1],1;" : "=r"(idx) : "l"(g_flag + (q == 3 ? FL_CINIT : rbq * 16 + FL_CW + q)) : "memory");
                    if ((int)idx < n) {
                        if (q == 3) task = 3 | (idx << 2);
                        else if (q == 1) task = 1 | (rbq << 2) | (idx << 6);
                        else task = q | (rbq << 2) | ((idx % 3) << 6) | ((idx / 3) << 11);
                    }
                }
                task = __shfl_sync(~0u, task, 0);
                idle = 0;
                if (task < 0) continue;
            } else {
                if (!open || ++idle > (1 << 16)) task = -2;
                else { __nanosleep(100); continue; }
            }
            if (lane == 0) {
                const int type = task & 3, rb = (task >> 2) & 15, nt = (task >> 6) & 31, ks = (task >> 11) & 15;
                if (task < 0 || type == 3) {
                    const int st = it % G_ST;
                    mbar_wait(bar_empty + 8 * st, ((it / G_ST) & 1) ^ 1, dead);
                    stage_task[st] = task;
                    mbar_arrive(bar_full + 8 * st);
                    it++;
                } else {
                    asm volatile("fence.proxy.async;" ::: "memory");
                    int KS, tot;
                    const uint8_t* A;
                    const CUtensorMap* tm;
                    if (type == 0) { KS = ks_w(rb); tot = 64; A = g_ox + (size_t)rb * 64 * 16384; tm = &tmWo; }
                    else if (type == 1) { KS = 1; tot = 9; A = g_hb + (size_t)rb * 9 * 16384; tm = &tmW1; }
                    else { KS = ks_f(rb); tot = 72; A = g_ff + (size_t)rb * 72 * 16384; tm = &tmW2; }
                    const int kp = kpart(tot, KS), k0 = ks * kp, k1 = ks == KS - 1 ? tot : k0 + kp;
                    for (int k = k0; k < k1; k++, it++) {
                        const int st = it % G_ST;
                        mbar_wait(bar_empty + 8 * st, ((it / G_ST) & 1) ^ 1, dead);
                        stage_task[st] = task;
                        const uint32_t a = sb + st * G_STAGE, bb = a + 16384, fb = bar_full + 8 * st;
                        const bool aux = type == 1 && k == 0;
                        mbar_expect_tx(fb, G_STAGE + (aux ? 4608 : 0));
                        bulk_g2s(a, A + (size_t)k * 16384, 16384, fb);
#pragma unroll
                        for (int i = 0; i < 3; i++) tma2d(bb + i * 8192, tm, nt * 192 + i * 64, k * 64, fb);
                        if (aux) {
                            bulk_g2s(sb + T_AUX + (nf1 & 1) * 4608, g_stat + rb * 384, 3072, fb);
                            bulk_g2s(sb + T_AUX + (nf1 & 1) * 4608 + 3072, g_cb + nt * 192, 1536, fb);
                            nf1++;
                        }
                    }
                    if (type != 1 && ks == KS - 1) {
                        const uint8_t* part = reinterpret_cast<const uint8_t*>(g_part + (size_t)(((type >> 1) * 16 + rb) * 3 + nt) * 24 * 256);
                        for (int e = 0; e < 4; e++, it++) {
                            const int st = it % G_ST;
                            mbar_wait(bar_empty + 8 * st, ((it / G_ST) & 1) ^ 1, dead);
                            const uint32_t a = sb + st * G_STAGE, fb = bar_full + 8 * st;
                            mbar_expect_tx(fb, e < 2 ? 32768 : 40960);
                            if (e < 2) {
                                for (int i = 2 * e; i < (e == 0 ? 2 : 3); i++) {
                                    if (type == 0) tma2d(a + (i & 1) * 16384, &tmX, nt * 192 + i * 64, rb * 128, fb);
                                    else bulk_g2s(a + (i & 1) * 16384, g_hb + (size_t)(rb * 9 + nt * 3 + i) * 16384, 16384, fb);
                                }
                            }
                            if (e == 1) {
                                const uint32_t* dn = g_flag + rb * 16 + FL_DONE + (type >> 1) * 3 + nt;
                                int n = 0;
                                while (ld_acquire1(dn) < (uint32_t)(KS - 1)) { if (++n > SPIN_LIMIT) { dead = 1; break; } __nanosleep(40); }
                                asm volatile("fence.proxy.async;" ::: "memory");
                                bulk_g2s(a + 16384, part + 81920, 16384, fb);
                            } else if (e >= 2) bulk_g2s(a, part + (e - 2) * 40960, 40960, fb);
                        }
                    }
                }
            }
            it = __shfl_sync(~0u, it, 0);
            if (task < 0) break;
        }
      } else if (warp == 9) {
        if (lane == 0) {
            uint32_t ph = 0;
            while (true) {
                int n = 0;
                while (!mbar_try(bar_sfull, ph)) { if (++n > (SPIN_LIMIT << 4)) { dead = 1; break; } }
                if (dead) break;
                const int task = *store_task;
                if (task < 0) break;
                const int type = task & 3, rb = (task >> 2) & 15, nt = (task >> 6) & 31, ks = (task >> 11) & 15;
                uint32_t* flag = nullptr;
                bool stored = true;
                if (type == 3) { flag = g_flag + FL_INIT; stored = false; }
                else if (type == 1) { flag = g_flag + rb * 16 + FL_FF; bulk_s2g(g_ff + (size_t)(rb * 72 + nt * 3) * 16384, sb + T_STG, 49152); }
                else if (ks < (type == 0 ? ks_w(rb) : ks_f(rb)) - 1) { flag = g_flag + rb * 16 + FL_DONE + (type >> 1) * 3 + nt; stored = false; }
                else if (type == 0) { flag = g_flag + rb * 16 + FL_H; bulk_s2g(g_hb + (size_t)(rb * 9 + nt * 3) * 16384, sb + T_STG, 49152); }
                else for (int i = 0; i < 3; i++) tma2d_store(&tmOut, sb + T_STG + i * 16384, nt * 192 + i * 64, rb * 128);
                if (stored) {
                    asm volatile("cp.async.bulk.commit_group;\ncp.async.bulk.wait_group.read 0;" ::: "memory");
                    mbar_arrive(bar_sempty);
                    asm volatile("cp.async.bulk.wait_group 0;\nfence.proxy.async;" ::: "memory");
                } else mbar_arrive(bar_sempty);
                if (flag) asm volatile("red.release.gpu.global.add.u32 [%0],1;" ::"l"(flag) : "memory");
                ph ^= 1;
            }
            pdl_wait();
            asm volatile("fence.acq_rel.gpu;" ::: "memory");
            if (atomicAdd(g_flag + FL_EXIT, 1u) == gridDim.x - 1) {
                for (int i = 0; i < 17 * 4; i++) reinterpret_cast<uint4*>(g_flag)[i] = make_uint4(0, 0, 0, 0);
            }
        }
      }
    } else {
        asm volatile("setmaxnreg.inc.sync.aligned.u32 232;");
        const int wg = warp >> 2, g = lane >> 2, t = lane & 3;
        const int lr = wg * 64 + (warp & 3) * 16 + g;
        const uint32_t mrow = (wg * 64 + (warp & 3) * 16 + ((lane >> 3) & 1) * 8 + (lane & 7)) * 128;
        const uint32_t mchk = lane >> 4, mxor = lane & 7;
        for (int i = tid; i < DM; i += 256) reinterpret_cast<float*>(smem + T_B2)[i] = __bfloat162float(b2[i]);
        bar_sync(1, 256);
        uint32_t it = 0, sph = 1, nf1 = 0;
        while (true) {
            {
                int n = 0;
                while (!mbar_try(bar_full + 8 * (it % G_ST), (it / G_ST) & 1)) { if (++n > (SPIN_LIMIT << 4)) { dead = 1; break; } }
            }
            const int task = dead ? -1 : stage_task[it % G_ST];
            if (task < 0) {
                mbar_wait(bar_sempty, sph, dead);
                if (tid == 0) *store_task = -1;
                mbar_arrive(bar_sfull);
                break;
            }
            const int type = task & 3, rb = (task >> 2) & 15, nt = (task >> 6) & 31, ks = (task >> 11) & 15;
            if (type == 3) {
                const int idx = task >> 2;
                __syncwarp();
                if (lane == 0) mbar_arrive(bar_empty + 8 * (it % G_ST));
                it++;
                mbar_wait(bar_sempty, sph, dead); sph ^= 1;
                float a8[8] = {0.f, 0.f, 0.f, 0.f, 0.f, 0.f, 0.f, 0.f};
                const uint4* src = reinterpret_cast<const uint4*>(w1 + idx * 128 + (tid & 15) * 8);
#pragma unroll 12
                for (int k = tid >> 4; k < DM; k += 16) {
                    const uint4 v = src[(size_t)k * (FF / 8)];
                    const uint32_t wv[4] = {v.x, v.y, v.z, v.w};
#pragma unroll
                    for (int j = 0; j < 4; j++) { a8[2 * j] += bf_lo(wv[j]); a8[2 * j + 1] += bf_hi(wv[j]); }
                }
                float* red = reinterpret_cast<float*>(smem + T_STG);
#pragma unroll
                for (int j = 0; j < 8; j++) red[(tid >> 4) * 128 + (tid & 15) * 8 + j] = a8[j];
                bar_sync(1, 256);
                if (tid < 128) {
                    float sum = 0.f;
#pragma unroll
                    for (int j = 0; j < 16; j++) sum += red[j * 128 + tid];
                    g_cb[idx * 128 + tid] = make_float2(sum, __bfloat162float(b1[idx * 128 + tid]));
                }
                for (int u = idx; u < 96; u += NINIT) {
                    const int rbu = (u / 3) & 15;
                    if ((u < 48 ? ks_w(rbu) : ks_f(rbu)) > 2)
                        for (int j = 0; j < 24; j++) g_part[((size_t)u * 24 + j) * 256 + tid] = make_float4(0.f, 0.f, 0.f, 0.f);
                }
                if (tid == 0) *store_task = task;
                mbar_arrive(bar_sfull);
                TLOG_END();
                continue;
            }
            const int KS = type == 0 ? ks_w(rb) : (type == 1 ? 1 : ks_f(rb));
            const int tot = type == 0 ? 64 : (type == 1 ? 9 : 72);
            const int kp = kpart(tot, KS);
            const int nk = ks == KS - 1 ? tot - ks * kp : kp;
            float acc[96];
            for (int k = 0; k < nk; k++, it++) {
                const int st = it % G_ST;
                mbar_wait(bar_full + 8 * st, (it / G_ST) & 1, dead);
                const uint32_t a = sb + st * G_STAGE + wg * 8192, b = sb + st * G_STAGE + 16384;
                const uint64_t da = mk_desc(a, 16, 1024), db = mk_desc(b, 8192, 1024);
                wg_fence();
#pragma unroll
                for (int kk = 0; kk < 4; kk++) wgmma_n192_ss(acc, da + kk * 2, db + kk * 128, (k | kk) != 0);
                wg_commit();
                if (k > 0) {
                    wg_wait<1>();
                    if (lane == 0) mbar_arrive(bar_empty + 8 * ((it - 1) % G_ST));
                }
            }
            wg_wait<0>();
            if (lane == 0) mbar_arrive(bar_empty + 8 * ((it - 1) % G_ST));
            if (ks < KS - 1) {
                float4* part = g_part + (size_t)(((type >> 1) * 16 + rb) * 3 + nt) * 24 * 256 + tid;
                if (KS == 2) {
#pragma unroll
                    for (int j = 0; j < 24; j++) __stcg(part + j * 256, make_float4(acc[4 * j], acc[4 * j + 1], acc[4 * j + 2], acc[4 * j + 3]));
                } else {
#pragma unroll
                    for (int j = 0; j < 24; j++)
                        asm volatile("red.relaxed.gpu.global.add.v4.f32 [%0],{%1,%2,%3,%4};" ::"l"(part + j * 256), "f"(acc[4 * j]), "f"(acc[4 * j + 1]),
                                     "f"(acc[4 * j + 2]), "f"(acc[4 * j + 3]) : "memory");
                }
                mbar_wait(bar_sempty, sph, dead); sph ^= 1;
                if (tid == 0) *store_task = task;
                mbar_arrive(bar_sfull);
                TLOG_END();
                continue;
            }
            uint32_t pk[48];
            if (type != 1) {
#pragma unroll
                for (int e = 0; e < 4; e++, it++) {
                    const int st = it % G_ST;
                    mbar_wait(bar_full + 8 * st, (it / G_ST) & 1, dead);
                    const uint32_t a = sb + st * G_STAGE;
                    if (e < 2) {
#pragma unroll
                        for (int j = e * 16; j < (e == 0 ? 16 : 24); j += 2) {
                            uint32_t rr[4];
                            ldsm4(rr, a + ((j >> 3) & 1) * 16384 + mrow + ((((j & 7) + mchk) ^ mxor) << 4));
                            acc[4 * j] += bf_lo(rr[0]); acc[4 * j + 1] += bf_hi(rr[0]); acc[4 * j + 2] += bf_lo(rr[1]); acc[4 * j + 3] += bf_hi(rr[1]);
                            acc[4 * j + 4] += bf_lo(rr[2]); acc[4 * j + 5] += bf_hi(rr[2]); acc[4 * j + 6] += bf_lo(rr[3]); acc[4 * j + 7] += bf_hi(rr[3]);
                        }
                    }
                    if (e >= 1) {
                        const int j0 = e == 1 ? 20 : (e - 2) * 10, jn = e == 1 ? 4 : 10;
#pragma unroll
                        for (int j = 0; j < jn; j++) {
                            const float4 pv = lds128f(a + (e == 1 ? 16384 : 0) + j * 4096 + tid * 16);
                            acc[4 * (j0 + j)] += pv.x; acc[4 * (j0 + j) + 1] += pv.y; acc[4 * (j0 + j) + 2] += pv.z; acc[4 * (j0 + j) + 3] += pv.w;
                        }
                    }
                    __syncwarp();
                    if (lane == 0) mbar_arrive(bar_empty + 8 * st);
                }
                if (type == 2) {
#pragma unroll
                    for (int j = 0; j < 24; j++) {
                        const float2 bv = lds64f(sb + T_B2 + (nt * 192 + j * 8 + 2 * t) * 4);
                        pk[2 * j] = pack_bf16(acc[4 * j] + bv.x, acc[4 * j + 1] + bv.y);
                        pk[2 * j + 1] = pack_bf16(acc[4 * j + 2] + bv.x, acc[4 * j + 3] + bv.y);
                    }
                } else {
                    float sm0 = 0.f, sm1 = 0.f;
#pragma unroll
                    for (int j = 0; j < 24; j++) {
                        pk[2 * j] = pack_bf16(acc[4 * j], acc[4 * j + 1]);
                        pk[2 * j + 1] = pack_bf16(acc[4 * j + 2], acc[4 * j + 3]);
                        sm0 += bf_lo(pk[2 * j]) + bf_hi(pk[2 * j]);
                        sm1 += bf_lo(pk[2 * j + 1]) + bf_hi(pk[2 * j + 1]);
                    }
                    sm0 += __shfl_xor_sync(~0u, sm0, 1); sm1 += __shfl_xor_sync(~0u, sm1, 1);
                    sm0 += __shfl_xor_sync(~0u, sm0, 2); sm1 += __shfl_xor_sync(~0u, sm1, 2);
                    sm0 *= (1.f / 192.f); sm1 *= (1.f / 192.f);
                    float q0 = 0.f, q1 = 0.f;
#pragma unroll
                    for (int j = 0; j < 24; j++) {
                        float d;
                        d = bf_lo(pk[2 * j]) - sm0; q0 += d * d;
                        d = bf_hi(pk[2 * j]) - sm0; q0 += d * d;
                        d = bf_lo(pk[2 * j + 1]) - sm1; q1 += d * d;
                        d = bf_hi(pk[2 * j + 1]) - sm1; q1 += d * d;
                    }
                    q0 += __shfl_xor_sync(~0u, q0, 1); q1 += __shfl_xor_sync(~0u, q1, 1);
                    q0 += __shfl_xor_sync(~0u, q0, 2); q1 += __shfl_xor_sync(~0u, q1, 2);
                    if (t == 0) {
                        g_stat[(rb * 3 + nt) * 128 + lr] = make_float2(sm0, q0);
                        g_stat[(rb * 3 + nt) * 128 + lr + 8] = make_float2(sm1, q1);
                    }
                }
            } else {
                const uint32_t aux = sb + T_AUX + (nf1 & 1) * 4608;
                nf1++;
                float2 s0[3], s1[3];
#pragma unroll
                for (int i = 0; i < 3; i++) { s0[i] = lds64f(aux + (i * 128 + lr) * 8); s1[i] = lds64f(aux + (i * 128 + lr + 8) * 8); }
                const float mean0 = (s0[0].x + s0[1].x + s0[2].x) * (1.f / 3.f), mean1 = (s1[0].x + s1[1].x + s1[2].x) * (1.f / 3.f);
                float m20 = s0[0].y + s0[1].y + s0[2].y, m21 = s1[0].y + s1[1].y + s1[2].y;
#pragma unroll
                for (int i = 0; i < 3; i++) { m20 += 192.f * (s0[i].x - mean0) * (s0[i].x - mean0); m21 += 192.f * (s1[i].x - mean1) * (s1[i].x - mean1); }
                const float rstd0 = rsqrtf(m20 * (1.f / DM) + 1e-5f), rstd1 = rsqrtf(m21 * (1.f / DM) + 1e-5f);
#pragma unroll
                for (int j = 0; j < 24; j++) {
                    const float4 c4 = lds128f(aux + 3072 + (j * 8 + 2 * t) * 8);
                    pk[2 * j] = pack_bf16(gelu_tanh(fmaf(rstd0, fmaf(-mean0, c4.x, acc[4 * j]), c4.y)),
                                          gelu_tanh(fmaf(rstd0, fmaf(-mean0, c4.z, acc[4 * j + 1]), c4.w)));
                    pk[2 * j + 1] = pack_bf16(gelu_tanh(fmaf(rstd1, fmaf(-mean1, c4.x, acc[4 * j + 2]), c4.y)),
                                              gelu_tanh(fmaf(rstd1, fmaf(-mean1, c4.z, acc[4 * j + 3]), c4.w)));
                }
            }
            mbar_wait(bar_sempty, sph, dead); sph ^= 1;
#pragma unroll
            for (int j = 0; j < 24; j += 2)
                stsm4(sb + T_STG + (j >> 3) * 16384 + mrow + ((((j & 7) + mchk) ^ mxor) << 4), pk[2 * j], pk[2 * j + 1], pk[2 * j + 2], pk[2 * j + 3]);
            fence_async();
            if (tid == 0) *store_task = task;
            mbar_arrive(bar_sfull);
            TLOG_END();
        }
    }
}

typedef CUresult (*EncodeFn)(CUtensorMap*, CUtensorMapDataType, cuuint32_t, void*, const cuuint64_t*, const cuuint64_t*,
                             const cuuint32_t*, const cuuint32_t*, CUtensorMapInterleave, CUtensorMapSwizzle,
                             CUtensorMapL2promotion, CUtensorMapFloatOOBfill);

void make_map(EncodeFn enc, CUtensorMap* tm, const void* ptr, uint64_t inner, uint64_t outer, uint32_t box_inner, uint32_t box_outer) {
    cuuint64_t dims[2] = {inner, outer};
    cuuint64_t strides[1] = {inner * 2};
    cuuint32_t box[2] = {box_inner, box_outer};
    cuuint32_t es[2] = {1, 1};
    enc(tm, CU_TENSOR_MAP_DATA_TYPE_BFLOAT16, 2, const_cast<void*>(ptr), dims, strides, box, es, CU_TENSOR_MAP_INTERLEAVE_NONE,
        CU_TENSOR_MAP_SWIZZLE_128B, CU_TENSOR_MAP_L2_PROMOTION_L2_256B, CU_TENSOR_MAP_FLOAT_OOB_FILL_NONE);
}

}

extern "C" void kernel_launch(void* const* d_in, const int* in_sizes, int n_in, void* d_out, int out_size) {
    const __nv_bfloat16* x = (const __nv_bfloat16*)d_in[0];
    const __nv_bfloat16* mem0 = (const __nv_bfloat16*)d_in[1];
    const __nv_bfloat16* Wq = (const __nv_bfloat16*)d_in[2];
    const __nv_bfloat16* Wk = (const __nv_bfloat16*)d_in[3];
    const __nv_bfloat16* Wv = (const __nv_bfloat16*)d_in[4];
    const __nv_bfloat16* Wo = (const __nv_bfloat16*)d_in[5];
    const __nv_bfloat16* w1 = (const __nv_bfloat16*)d_in[8];
    const __nv_bfloat16* b1 = (const __nv_bfloat16*)d_in[9];
    const __nv_bfloat16* w2 = (const __nv_bfloat16*)d_in[10];
    const __nv_bfloat16* b2 = (const __nv_bfloat16*)d_in[11];
    __nv_bfloat16* out = (__nv_bfloat16*)d_out;
    cudaStream_t stream = cudaStreamPerThread;

    static EncodeFn enc = nullptr;
    if (!enc) {
        cudaDriverEntryPointQueryResult qr;
        void* fn = nullptr;
        cudaGetDriverEntryPoint("cuTensorMapEncodeTiled", &fn, cudaEnableDefault, &qr);
        enc = (EncodeFn)fn;
        cudaFuncSetAttribute(k_chain, cudaFuncAttributeMaxDynamicSharedMemorySize, SM_CHAIN_BYTES);
        cudaFuncSetAttribute(k_tail, cudaFuncAttributeMaxDynamicSharedMemorySize, T_SMEM);
    }
    CUtensorMap tWq, tWk, tWv, tWo, tW1, tW2, tX, tOut;
    make_map(enc, &tWq, Wq, HD, DM, 64, 192);
    make_map(enc, &tWk, Wk, HD, DM, 64, 192);
    make_map(enc, &tWv, Wv, HD, DM, 64, 192);
    make_map(enc, &tX, x, DM, SEQ, 64, 128);
    make_map(enc, &tOut, out, DM, SEQ, 64, 128);
    make_map(enc, &tWo, Wo, DM, HD, 64, 64);
    make_map(enc, &tW1, w1, FF, DM, 64, 64);
    make_map(enc, &tW2, w2, DM, FF, 64, 64);

    {
        cudaLaunchConfig_t cfg = {};
        cfg.gridDim = dim3(96); cfg.blockDim = dim3(384); cfg.dynamicSmemBytes = SM_CHAIN_BYTES; cfg.stream = stream;
        void* px;
        cudaGetSymbolAddress(&px, g_xch);
        uint8_t* xb = reinterpret_cast<uint8_t*>((reinterpret_cast<uintptr_t>(px) + 65535) & ~(uintptr_t)65535);
        cudaLaunchKernelEx(&cfg, k_chain, tWq, tWk, tWv, tWo, x, mem0, xb);
    }
    {
        cudaLaunchConfig_t cfg = {};
        cfg.gridDim = dim3(132); cfg.blockDim = dim3(384); cfg.dynamicSmemBytes = T_SMEM; cfg.stream = stream;
        cudaLaunchAttribute at[1];
        at[0].id = cudaLaunchAttributeProgrammaticStreamSerialization;
        at[0].val.programmaticStreamSerializationAllowed = 1;
        cfg.attrs = at; cfg.numAttrs = 1;
        cudaLaunchKernelEx(&cfg, k_tail, tWo, tW1, tW2, tX, tOut, w1, b1, b2);
    }
}
```

```cpp
#include <cuda_runtime.h>
#include <cuda_bf16.h>
#include <cuda.h>
#include <stdint.h>

namespace {

constexpr int SEQ = 2048, DM = 576, NH = 32, DH = 128, NSEG = 64, FF = 4608, HD = 4096;
constexpr int XN_SEG_BYTES = 32 * DM * 2;
constexpr int SPIN_LIMIT = 1 << 20;

__device__ __align__(1024) uint8_t g_xn[NSEG * XN_SEG_BYTES];
__device__ __align__(1024) uint8_t g_ox[SEQ * HD * 2];
__device__ __align__(1024) uint8_t g_xch[(96 + 3) * 65536];
__device__ uint32_t g_tab[128];
__device__ __align__(1024) uint8_t g_hb[SEQ * DM * 2];
__device__ __align__(1024) uint8_t g_ff[SEQ * FF * 2];
__device__ __align__(1024) float4 g_part[2 * 16 * 3 * 24 * 256];
__device__ __align__(128) float2 g_stat[16 * 9 * 128];
__device__ __align__(128) float2 g_cb[FF];
constexpr int FL_OX = 0, FL_H = 1, FL_FF = 2, FL_CW = 4, FL_C1 = 5, FL_C2 = 6, FL_DONE = 8  , FL_INIT = 512, FL_CINIT = 513, FL_EXIT = 514;
__device__ __align__(128) uint32_t g_flag[17 * 32];
#define TLOG_END()
#define PSTAMP(i)

__device__ __forceinline__ uint32_t smem_u32(const void* p) { return (uint32_t)__cvta_generic_to_shared(p); }
__device__ __forceinline__ uint32_t mapa(uint32_t a, uint32_t r) {
    uint32_t o; asm("mapa.shared::cluster.u32 %0,%1,%2;" : "=r"(o) : "r"(a), "r"(r)); return o;
}
__device__ __forceinline__ void mbar_init(uint32_t bar, uint32_t cnt) {
    asm volatile("mbarrier.init.shared::cta.b64 [%0],%1;" ::"r"(bar), "r"(cnt) : "memory");
}
__device__ __forceinline__ void mbar_expect_tx(uint32_t bar, uint32_t bytes) {
    asm volatile("mbarrier.arrive.expect_tx.shared::cta.b64 _,[%0],%1;" ::"r"(bar), "r"(bytes) : "memory");
}
__device__ __forceinline__ void mbar_arrive(uint32_t bar) {
    asm volatile("mbarrier.arrive.shared::cta.b64 _,[%0];" ::"r"(bar) : "memory");
}
__device__ __forceinline__ bool mbar_try(uint32_t bar, uint32_t ph) {
    uint32_t ok;
    asm volatile("{.reg .pred p; mbarrier.try_wait.parity.shared::cta.b64 p,[%1],%2; selp.u32 %0,1,0,p;}"
                 : "=r"(ok) : "r"(bar), "r"(ph) : "memory");
    return ok;
}
__device__ __forceinline__ bool mbar_try_cluster(uint32_t bar, uint32_t ph) {
    uint32_t ok;
    asm volatile("{.reg .pred p; mbarrier.try_wait.parity.acquire.cluster.shared::cta.b64 p,[%1],%2; selp.u32 %0,1,0,p;}"
                 : "=r"(ok) : "r"(bar), "r"(ph) : "memory");
    return ok;
}
__device__ __forceinline__ void mbar_wait(uint32_t bar, uint32_t ph, int& dead) {
    if (mbar_try(bar, ph)) return;
    int n = dead ? SPIN_LIMIT : 0;
#pragma unroll 1
    while (!mbar_try(bar, ph)) { if (++n > SPIN_LIMIT) { dead = 1; break; } }
}
__device__ __forceinline__ uint32_t opaque(uint32_t v, int lane) { return __shfl_sync(~0u, v, lane); }
__device__ __forceinline__ void mbar_wait_cluster(uint32_t bar, uint32_t ph, int& dead) {
    if (dead) return;
    int n = 0;
    while (!mbar_try_cluster(bar, ph)) { if (++n > SPIN_LIMIT) { dead = 1; break; } }
}
__device__ __forceinline__ void bar_sync(int id, int n) { asm volatile("bar.sync %0,%1;" ::"r"(id), "r"(n) : "memory"); }
__device__ __forceinline__ void bar_arrive(int id, int n) { asm volatile("bar.arrive %0,%1;" ::"r"(id), "r"(n) : "memory"); }
__device__ __forceinline__ void cluster_sync() {
    asm volatile("barrier.cluster.arrive.release.aligned;\nbarrier.cluster.wait.acquire.aligned;" ::: "memory");
}
__device__ __forceinline__ void fence_async() { asm volatile("fence.proxy.async.shared::cta;" ::: "memory"); }

__device__ __forceinline__ void ldsm4(uint32_t (&r)[4], uint32_t a) {
    asm volatile("ldmatrix.sync.aligned.m8n8.x4.shared.b16 {%0,%1,%2,%3},[%4];"
                 : "=r"(r[0]), "=r"(r[1]), "=r"(r[2]), "=r"(r[3]) : "r"(a) : "memory");
}
__device__ __forceinline__ void ldsm4t(uint32_t (&r)[4], uint32_t a) {
    asm volatile("ldmatrix.sync.aligned.m8n8.x4.trans.shared.b16 {%0,%1,%2,%3},[%4];"
                 : "=r"(r[0]), "=r"(r[1]), "=r"(r[2]), "=r"(r[3]) : "r"(a) : "memory");
}
__device__ __forceinline__ void stsm4(uint32_t a, uint32_t r0, uint32_t r1, uint32_t r2, uint32_t r3) {
    asm volatile("stmatrix.sync.aligned.m8n8.x4.shared.b16 [%0],{%1,%2,%3,%4};" ::"r"(a), "r"(r0), "r"(r1), "r"(r2), "r"(r3) : "memory");
}
__device__ __forceinline__ void stsm4t(uint32_t a, uint32_t r0, uint32_t r1, uint32_t r2, uint32_t r3) {
    asm volatile("stmatrix.sync.aligned.m8n8.x4.trans.shared.b16 [%0],{%1,%2,%3,%4};" ::"r"(a), "r"(r0), "r"(r1), "r"(r2), "r"(r3) : "memory");
}
__device__ __forceinline__ void mma16(float (&d)[4], uint32_t a0, uint32_t a1, uint32_t a2, uint32_t a3, uint32_t b0, uint32_t b1) {
    asm volatile("mma.sync.aligned.m16n8k16.row.col.f32.bf16.bf16.f32 {%0,%1,%2,%3},{%4,%5,%6,%7},{%8,%9},{%0,%1,%2,%3};"
                 : "+f"(d[0]), "+f"(d[1]), "+f"(d[2]), "+f"(d[3]) : "r"(a0), "r"(a1), "r"(a2), "r"(a3), "r"(b0), "r"(b1));
}
__device__ __forceinline__ void mma8(float (&d)[4], uint32_t a0, uint32_t a1, uint32_t b0) {
    asm volatile("mma.sync.aligned.m16n8k8.row.col.f32.bf16.bf16.f32 {%0,%1,%2,%3},{%4,%5},{%6},{%0,%1,%2,%3};"
                 : "+f"(d[0]), "+f"(d[1]), "+f"(d[2]), "+f"(d[3]) : "r"(a0), "r"(a1), "r"(b0));
}
__device__ __forceinline__ uint32_t pack_bf16(float lo, float hi) {
    uint32_t r; asm("cvt.rn.bf16x2.f32 %0,%1,%2;" : "=r"(r) : "f"(hi), "f"(lo)); return r;
}
__device__ __forceinline__ float bf_lo(uint32_t w) { return __uint_as_float(w << 16); }
__device__ __forceinline__ float bf_hi(uint32_t w) { return __uint_as_float(w & 0xffff0000u); }
__device__ __forceinline__ float ex2(float x) { float r; asm("ex2.approx.ftz.f32 %0,%1;" : "=f"(r) : "f"(x)); return r; }
__device__ __forceinline__ void st_async32(uint32_t dst, uint32_t v, uint32_t bar) {
    asm volatile("st.async.shared::cluster.mbarrier::complete_tx::bytes.u32 [%0],%1,[%2];" ::"r"(dst), "r"(v), "r"(bar) : "memory");
}
__device__ __forceinline__ void bulk_g2s(uint32_t dst, const void* src, uint32_t bytes, uint32_t bar) {
    asm volatile("cp.async.bulk.shared::cluster.global.mbarrier::complete_tx::bytes [%0],[%1],%2,[%3];"
                 ::"r"(dst), "l"(src), "r"(bytes), "r"(bar) : "memory");
}
__device__ __forceinline__ void bulk_g2s_mc(uint32_t dst, const void* src, uint32_t bytes, uint32_t bar, uint16_t mask) {
    asm volatile("cp.async.bulk.shared::cluster.global.mbarrier::complete_tx::bytes.multicast::cluster [%0],[%1],%2,[%3],%4;"
                 ::"r"(dst), "l"(src), "r"(bytes), "r"(bar), "h"(mask) : "memory");
}
__device__ __forceinline__ void bulk_s2s(uint32_t dst, uint32_t src, uint32_t bytes, uint32_t bar) {
    asm volatile("cp.async.bulk.shared::cluster.shared::cta.mbarrier::complete_tx::bytes [%0],[%1],%2,[%3];"
                 ::"r"(dst), "r"(src), "r"(bytes), "r"(bar) : "memory");
}
__device__ __forceinline__ void tma2d(uint32_t dst, const CUtensorMap* tm, int c0, int c1, uint32_t bar) {
    asm volatile("cp.async.bulk.tensor.2d.shared::cluster.global.mbarrier::complete_tx::bytes [%0],[%1,{%3,%4}],[%2];"
                 ::"r"(dst), "l"(tm), "r"(bar), "r"(c0), "r"(c1) : "memory");
}
__device__ __forceinline__ void cp_async16(uint32_t dst, const void* src) {
    asm volatile("cp.async.cg.shared.global [%0],[%1],16;" ::"r"(dst), "l"(src) : "memory");
}
__device__ __forceinline__ uint4 ld_relaxed4(const void* p) {
    uint4 v;
    asm volatile("ld.relaxed.gpu.global.v4.u32 {%0,%1,%2,%3},[%4];" : "=r"(v.x), "=r"(v.y), "=r"(v.z), "=r"(v.w) : "l"(p) : "memory");
    return v;
}
__device__ __forceinline__ void st_relaxed2(void* p, uint32_t a, uint32_t b) {
    asm volatile("st.relaxed.gpu.global.v2.u32 [%0],{%1,%2};" ::"l"(p), "r"(a), "r"(b) : "memory");
}
__device__ __forceinline__ void st_relaxed1(void* p, uint32_t a) {
    asm volatile("st.relaxed.gpu.global.u32 [%0],%1;" ::"l"(p), "r"(a) : "memory");
}
__device__ __forceinline__ uint32_t ld_relaxed1(const void* p) {
    uint32_t v; asm volatile("ld.relaxed.gpu.global.u32 %0,[%1];" : "=r"(v) : "l"(p) : "memory"); return v;
}
__device__ __forceinline__ void red_add1(uint32_t* p) { asm volatile("red.relaxed.gpu.global.add.u32 [%0],1;" ::"l"(p) : "memory"); }
__device__ __forceinline__ void sts128(uint32_t a, uint4 v) {
    asm volatile("st.shared.v4.u32 [%0],{%1,%2,%3,%4};" ::"r"(a), "r"(v.x), "r"(v.y), "r"(v.z), "r"(v.w) : "memory");
}
__device__ __forceinline__ uint4 lds128(uint32_t a) {
    uint4 v; asm volatile("ld.shared.v4.u32 {%0,%1,%2,%3},[%4];" : "=r"(v.x), "=r"(v.y), "=r"(v.z), "=r"(v.w) : "r"(a) : "memory");
    return v;
}
__device__ __forceinline__ void sts32f(uint32_t a, float v) { asm volatile("st.shared.f32 [%0],%1;" ::"r"(a), "f"(v) : "memory"); }
__device__ __forceinline__ float2 lds64f(uint32_t a) {
    float2 v; asm volatile("ld.shared.v2.f32 {%0,%1},[%2];" : "=f"(v.x), "=f"(v.y) : "r"(a) : "memory"); return v;
}
__device__ __forceinline__ void wg_fence() { asm volatile("wgmma.fence.sync.aligned;" ::: "memory"); }
__device__ __forceinline__ void wg_commit() { asm volatile("wgmma.commit_group.sync.aligned;" ::: "memory"); }
template <int N> __device__ __forceinline__ void wg_wait() { asm volatile("wgmma.wait_group.sync.aligned %0;" ::"n"(N) : "memory"); }
__device__ __forceinline__ uint64_t mk_desc(uint32_t addr, uint32_t lbo, uint32_t sbo) {
    return (uint64_t)((addr & 0x3FFFF) >> 4) | ((uint64_t)(lbo >> 4) << 16) | ((uint64_t)(sbo >> 4) << 32) | (1ull << 62);
}
__device__ __forceinline__ void wgmma_n32_rs(float (&d)[16], const uint32_t (&a)[4], uint64_t desc, int scale_d) {
    asm volatile("{.reg .pred p; setp.ne.b32 p,%21,0;\n"
                 "wgmma.mma_async.sync.aligned.m64n32k16.f32.bf16.bf16 "
                 "{%0,%1,%2,%3,%4,%5,%6,%7,%8,%9,%10,%11,%12,%13,%14,%15},{%16,%17,%18,%19},%20,p,1,1,0;}"
                 : "+f"(d[0]), "+f"(d[1]), "+f"(d[2]), "+f"(d[3]), "+f"(d[4]), "+f"(d[5]), "+f"(d[6]), "+f"(d[7]),
                   "+f"(d[8]), "+f"(d[9]), "+f"(d[10]), "+f"(d[11]), "+f"(d[12]), "+f"(d[13]), "+f"(d[14]), "+f"(d[15])
                 : "r"(a[0]), "r"(a[1]), "r"(a[2]), "r"(a[3]), "l"(desc), "r"(scale_d));
}
__device__ __forceinline__ void wgmma_n32_rs_tb(float (&d)[16], const uint32_t (&a)[4], uint64_t desc) {
    asm volatile("wgmma.mma_async.sync.aligned.m64n32k16.f32.bf16.bf16 "
                 "{%0,%1,%2,%3,%4,%5,%6,%7,%8,%9,%10,%11,%12,%13,%14,%15},{%16,%17,%18,%19},%20,1,1,1,1;"
                 : "+f"(d[0]), "+f"(d[1]), "+f"(d[2]), "+f"(d[3]), "+f"(d[4]), "+f"(d[5]), "+f"(d[6]), "+f"(d[7]),
                   "+f"(d[8]), "+f"(d[9]), "+f"(d[10]), "+f"(d[11]), "+f"(d[12]), "+f"(d[13]), "+f"(d[14]), "+f"(d[15])
                 : "r"(a[0]), "r"(a[1]), "r"(a[2]), "r"(a[3]), "l"(desc));
}
__device__ __forceinline__ void wgmma_n8_rs(float (&d)[4], uint32_t a0, uint32_t a1, uint32_t a2, uint32_t a3, uint64_t desc) {
    asm volatile("wgmma.mma_async.sync.aligned.m64n8k16.f32.bf16.bf16 {%0,%1,%2,%3},{%4,%5,%6,%7},%8,1,1,1,0;"
                 : "+f"(d[0]), "+f"(d[1]), "+f"(d[2]), "+f"(d[3]) : "r"(a0), "r"(a1), "r"(a2), "r"(a3), "l"(desc));
}
__device__ __forceinline__ void wgmma_n32_ss_tb0(float (&d)[16], uint64_t da, uint64_t desc) {
    asm volatile("wgmma.mma_async.sync.aligned.m64n32k16.f32.bf16.bf16 "
                 "{%0,%1,%2,%3,%4,%5,%6,%7,%8,%9,%10,%11,%12,%13,%14,%15},%16,%17,0,1,1,0,1;"
                 : "=f"(d[0]), "=f"(d[1]), "=f"(d[2]), "=f"(d[3]), "=f"(d[4]), "=f"(d[5]), "=f"(d[6]), "=f"(d[7]),
                   "=f"(d[8]), "=f"(d[9]), "=f"(d[10]), "=f"(d[11]), "=f"(d[12]), "=f"(d[13]), "=f"(d[14]), "=f"(d[15])
                 : "l"(da), "l"(desc));
}
__device__ __forceinline__ void wgmma_n32_ss(float (&d)[16], uint64_t da, uint64_t desc) {
    asm volatile("wgmma.mma_async.sync.aligned.m64n32k16.f32.bf16.bf16 "
                 "{%0,%1,%2,%3,%4,%5,%6,%7,%8,%9,%10,%11,%12,%13,%14,%15},%16,%17,1,1,1,0,0;"
                 : "+f"(d[0]), "+f"(d[1]), "+f"(d[2]), "+f"(d[3]), "+f"(d[4]), "+f"(d[5]), "+f"(d[6]), "+f"(d[7]),
                   "+f"(d[8]), "+f"(d[9]), "+f"(d[10]), "+f"(d[11]), "+f"(d[12]), "+f"(d[13]), "+f"(d[14]), "+f"(d[15])
                 : "l"(da), "l"(desc));
}
__device__ __forceinline__ void pdl_wait() { asm volatile("griddepcontrol.wait;" ::: "memory"); }
__device__ __forceinline__ void pdl_launch() { asm volatile("griddepcontrol.launch_dependents;" ::: "memory"); }

__device__ __forceinline__ void ln_load(uint4 (&v)[3], const __nv_bfloat16* __restrict__ x, int row, int lane) {
    const uint4* src = reinterpret_cast<const uint4*>(x + (size_t)row * DM);
#pragma unroll
    for (int i = 0; i < 3; i++) {
        v[i] = make_uint4(0, 0, 0, 0);
        if (lane + 32 * i < 72 && row < SEQ)
            asm volatile("ld.global.nc.v4.u32 {%0,%1,%2,%3},[%4];" : "=r"(v[i].x), "=r"(v[i].y), "=r"(v[i].z), "=r"(v[i].w) : "l"(src + lane + 32 * i));
    }
}
__device__ __forceinline__ void ln_row(const uint4 (&v)[3], int row, int lane) {
    float f[24];
    float sum = 0.f;
#pragma unroll
    for (int i = 0; i < 3; i++) {
        const uint32_t w[4] = {v[i].x, v[i].y, v[i].z, v[i].w};
#pragma unroll
        for (int j = 0; j < 4; j++) {
            f[i * 8 + 2 * j] = __uint_as_float(w[j] << 16);
            f[i * 8 + 2 * j + 1] = __uint_as_float(w[j] & 0xffff0000u);
            sum += f[i * 8 + 2 * j] + f[i * 8 + 2 * j + 1];
        }
    }
#pragma unroll
    for (int o = 16; o; o >>= 1) sum += __shfl_xor_sync(~0u, sum, o);
    const float mean = sum * (1.f / DM);
    float var = 0.f;
#pragma unroll
    for (int i = 0; i < 3; i++) {
        if (lane + 32 * i < 72) {
#pragma unroll
            for (int j = 0; j < 8; j++) { float d = f[i * 8 + j] - mean; var += d * d; }
        }
    }
#pragma unroll
    for (int o = 16; o; o >>= 1) var += __shfl_xor_sync(~0u, var, o);
    const float rstd = rsqrtf(var * (1.f / DM) + 1e-5f);
    const int seg = row >> 5, r = row & 31;
#pragma unroll
    for (int i = 0; i < 3; i++) {
        const int c = lane + 32 * i;
        if (c < 72) {
            uint4 o;
            o.x = pack_bf16((f[i * 8 + 0] - mean) * rstd, (f[i * 8 + 1] - mean) * rstd);
            o.y = pack_bf16((f[i * 8 + 2] - mean) * rstd, (f[i * 8 + 3] - mean) * rstd);
            o.z = pack_bf16((f[i * 8 + 4] - mean) * rstd, (f[i * 8 + 5] - mean) * rstd);
            o.w = pack_bf16((f[i * 8 + 6] - mean) * rstd, (f[i * 8 + 7] - mean) * rstd);
            *reinterpret_cast<uint4*>(g_xn + (size_t)seg * XN_SEG_BYTES + (c >> 3) * 4096 + r * 128 + (((c & 7) ^ (r & 7)) << 4)) = o;
        }
    }
}

constexpr int SM_XN = 0;
constexpr int SM_X = 73728;
constexpr int SM_MB = SM_X + 3 * 24576;
constexpr int SXR = 56;
constexpr int SMR = 80;
constexpr int SM_SX = SM_MB + 3 * 6144;
constexpr int SM_SXX = SM_SX + 8 * SMR * 4;
constexpr int SM_OT = SM_SXX + 16 * SXR * 4;
constexpr int SM_OX = SM_OT + 2048;
constexpr int SM_MAIN_END = SM_OX + 4096;
constexpr int SM_STG_W = XN_SEG_BYTES;
constexpr int SM_MEMT = SM_STG_W + 147456;
#define NREGK 33
constexpr int NREG_K = NREGK;
constexpr int SM_WS = SM_MEMT + 9216;
constexpr int SM_TAB = SM_WS + (36 - NREG_K) * 4096;
constexpr int SM_AUX = SM_TAB + 4096;
constexpr int SM_BAR = SM_AUX + 12288;
constexpr int SM_TIM = SM_BAR + 128;
constexpr int SM_CHAIN_BYTES = SM_TIM + 1024;
static_assert(SM_MAIN_END <= SM_MEMT && SM_TAB % 1024 == 0 && SM_STG_W % 1024 == 0, "smem");
static_assert(SM_CHAIN_BYTES <= 232448, "smem");
constexpr int BAR_MEM = 1, BAR_GO = 2, BAR_A = 3, BAR_B = 4, BAR_QD = 5, BAR_GO2 = 6, BAR_S = 7, BAR_U = 8, BAR_OX = 9;
#define BULK1 22

__device__ __forceinline__ uint32_t clk32() { uint32_t t; asm volatile("mov.u32 %0,%%clock;" : "=r"(t)::"memory"); return t; }
#define TSTAMP(i)
#define TFLUSH()
#define PIN(x) asm volatile("" : "+r"(x))
#define PINL(x) asm volatile("" : "+l"(x))

__device__ __forceinline__ uint2 ld_relaxed2(const void* p) {
    uint2 v;
    asm volatile("ld.relaxed.gpu.global.v2.u32 {%0,%1},[%2];" : "=r"(v.x), "=r"(v.y) : "l"(p) : "memory");
    return v;
}
__device__ __forceinline__ uint32_t ld_acquire1(const void* p) {
    uint32_t v; asm volatile("ld.acquire.gpu.global.u32 %0,[%1];" : "=r"(v) : "l"(p) : "memory"); return v;
}
__device__ __forceinline__ uint32_t xand(uint32_t a, uint32_t b, uint32_t m) {
    uint32_t r; asm("lop3.b32 %0,%1,%2,%3,0x42;" : "=r"(r) : "r"(a), "r"(b), "r"(m)); return r;
}
__device__ __forceinline__ uint32_t and3(uint32_t a, uint32_t b, uint32_t c) {
    uint32_t r; asm("lop3.b32 %0,%1,%2,%3,0x80;" : "=r"(r) : "r"(a), "r"(b), "r"(c)); return r;
}
__device__ __forceinline__ uint32_t settag(float v, uint32_t tag) {
    uint32_t r; asm("lop3.b32 %0,%1,0xfffffffe,%2,0xea;" : "=r"(r) : "r"(__float_as_uint(v)), "r"(tag)); return r;
}
__device__ __forceinline__ float rcp_fast(float x) { float r; asm("rcp.approx.ftz.f32 %0,%1;" : "=f"(r) : "f"(x)); return r; }
__device__ __forceinline__ void sts64f(uint32_t a, float x, float y) { asm volatile("st.shared.v2.f32 [%0],{%1,%2};" ::"r"(a), "f"(x), "f"(y) : "memory"); }

__device__ __forceinline__ uint32_t near_parity(uint8_t* blk, int cta) {
    uint32_t best[2] = {~0u, ~0u};
    for (int r = 0; r < 4; r++)
#pragma unroll
        for (int p = 0; p < 2; p++) {
            uint8_t* a = blk + (0xF000 ^ (p << 12)) + (cta & 31) * 128;
            uint32_t v, t1 = 0;
            const uint32_t t0 = clk32();
            asm volatile("atom.relaxed.gpu.global.add.u32 %0,[%1],1;" : "=r"(v) : "l"(a) : "memory");
            asm volatile("{.reg .pred p; setp.ne.u32 p,%1,0x7fffffff; @p mov.u32 %0,%%clock;}" : "+r"(t1) : "r"(v) : "memory");
            best[p] = min(best[p], t1 - t0);
        }
    return best[0] <= best[1] ? 0u : 1u;
}

template <int GRP>
__device__ __forceinline__ void xfinish(uint32_t sxa, uint32_t vaa, uint32_t vma, uint32_t st_w, uint32_t st_r, uint8_t* dst, int g, int t, int nbar) {
    constexpr int NB = GRP + 2;
    constexpr bool needB = (GRP >= 2);
    const float sc = 0.08838834764831845f * 1.4426950408889634f;
    bar_sync(BAR_A, nbar);
    float2 v[6];
#pragma unroll
    for (int b = 0; b < NB + 1; b++) v[b] = lds64f(sxa + b * 32);
    uint32_t f0[4], f1[4];
    ldsm4(f0, vma);
    v[1].x += v[0].x; v[1].y += v[0].y;
    if (2 * t > g) v[NB].x = -INFINITY;
    if (2 * t + 1 > g) v[NB].y = -INFINITY;
    float mx = fmaxf(v[1].x, v[1].y);
#pragma unroll
    for (int b = 2; b < NB + 1; b++) mx = fmaxf(mx, fmaxf(v[b].x, v[b].y));
    mx = fmaxf(mx, __shfl_xor_sync(~0u, mx, 1));
    mx = fmaxf(mx, __shfl_xor_sync(~0u, mx, 2));
    mx *= sc;
    uint32_t pk[5];
    float sum = 0.f;
#pragma unroll
    for (int b = 0; b < 5; b++) {
        if (b < NB) {
            float p0 = ex2(fmaf(v[b + 1].x, sc, -mx)), p1 = ex2(fmaf(v[b + 1].y, sc, -mx));
            sum += p0 + p1;
            pk[b] = pack_bf16(p0, p1);
        } else pk[b] = 0u;
    }
    float o[2][4] = {{0.f, 0.f, 0.f, 0.f}, {0.f, 0.f, 0.f, 0.f}};
    ldsm4(f1, vaa);
    mma8(o[0], f0[0], f0[1], pk[0]);
    mma8(o[1], f0[2], f0[3], pk[0]);
    ldsm4(f0, vaa + 256);
    sum += __shfl_xor_sync(~0u, sum, 1);
    mma16(o[0], f1[0], f1[1], f1[2], f1[3], pk[1], pk[2]);
    if (needB) ldsm4(f1, vaa + 4096);
    mma16(o[1], f0[0], f0[1], f0[2], f0[3], pk[1], pk[2]);
    if (needB) ldsm4(f0, vaa + 4096 + 256);
    sum += __shfl_xor_sync(~0u, sum, 2);
    if (needB) {
        mma16(o[0], f1[0], f1[1], f1[2], f1[3], pk[3], pk[4]);
        mma16(o[1], f0[0], f0[1], f0[2], f0[3], pk[3], pk[4]);
    }
    const float s0 = __shfl_sync(~0u, sum, 8 * t), s1 = __shfl_sync(~0u, sum, 8 * t + 4);
    const float i0 = rcp_fast(s0), i1 = rcp_fast(s1);
    stsm4t(st_w, pack_bf16(o[0][0] * i0, o[0][1] * i1), pack_bf16(o[0][2] * i0, o[0][3] * i1),
           pack_bf16(o[1][0] * i0, o[1][1] * i1), pack_bf16(o[1][2] * i0, o[1][3] * i1));
    __syncwarp();
    uint4 val = lds128(st_r);
    *reinterpret_cast<uint4*>(dst + GRP * 1024) = val;
}

__device__ __forceinline__ void xrest(uint32_t sb, uint32_t xs, uint32_t mb, int c, int h, int s, int w, int lane, int wg) {
    const int g = lane >> 2, t = lane & 3, m = lane >> 3, r = lane & 7;
    const uint32_t sxa = sb + SM_SXX + (g * SXR + 2 * t) * 4;
    const uint32_t vaa = xs + 16384 + (m >> 1) * 2048 + (32 * w + 8 * (m & 1) + r) * 16;
    const uint32_t vma = mb + 4096 + (32 * w + lane) * 16;
    const uint32_t st_w = sb + SM_OX + w * 512 + r * 64 + ((m ^ ((r >> 1) & 3)) << 4);
    const uint32_t st_r = sb + SM_OX + w * 512 + g * 64 + ((t ^ ((g >> 1) & 3)) << 4);
    uint8_t* dst = g_ox + (size_t)((s >> 2) * 64 + 2 * h + (w >> 1)) * 16384 + ((s & 3) * 32 + g) * 128 + ((((w & 1) * 4 + t) ^ g) << 4);
    if (wg == 0) xfinish<0>(sxa, vaa, vma, st_w + 2048, st_r + 2048, dst, g, t, 256);
    else if (c == 2) xfinish<1>(sxa + 8 * SXR * 4, vaa, vma, st_w, st_r, dst, g, t, 256);
    else if (c == 0) xfinish<3>(sxa + 8 * SXR * 4, vaa, vma, st_w, st_r, dst, g, t, 128);
    else xfinish<2>(sxa, vaa, vma, st_w, st_r, dst, g, t, 128);
}

__device__ __forceinline__ void xattn(uint32_t sb, uint32_t xs, uint32_t mb, uint32_t barq, uint32_t phq, int c, int h, int s, int w, int lane, int& dead) {
    const int g = lane >> 2, t = lane & 3, m = lane >> 3, r = lane & 7;
    if (w < 2) {
        const int kt = (c == 2) ? 0 : w, grp = (c == 2) ? w : 3 - c;
        const uint32_t kb = xs + 8192 + (2 * kt + (m & 1)) * 2048 + (8 * (m >> 1) + r) * 16;
        const uint32_t qb = xs + grp * 2048 + lane * 16;
        float c0[4] = {0.f, 0.f, 0.f, 0.f}, c1[4] = {0.f, 0.f, 0.f, 0.f};
#pragma unroll
        for (int j = 0; j < 4; j++) {
            uint32_t q[4], a[4], b[4];
            ldsm4t(q, qb + j * 512);
            ldsm4t(a, kb + j * 512);
            ldsm4t(b, kb + j * 512 + 256);
            mma16(c0, a[0], a[1], a[2], a[3], q[0], q[1]);
            mma16(c1, b[0], b[1], b[2], b[3], q[2], q[3]);
        }
        const uint32_t p = sb + SM_SXX + (((grp & 1) * 8 + 2 * t) * SXR + 16 + 16 * kt + g) * 4;
        sts32f(p, c0[0] + c1[0]);
        sts32f(p + SXR * 4, c0[1] + c1[1]);
        sts32f(p + 32, c0[2] + c1[2]);
        sts32f(p + SXR * 4 + 32, c0[3] + c1[3]);
        mbar_wait(barq, phq, dead);
    } else {
        const uint4 at = lds128(sb + SM_AUX + (128 + w * 32 + lane) * 16);
        const uint32_t qa = mb + at.y, ka = mb + at.w, sxw = at.z;
        mbar_wait(barq, phq, dead);
        uint32_t a[2][4];
        {
            uint32_t q[2][4];
            float c0[4] = {0.f, 0.f, 0.f, 0.f}, c1[4] = {0.f, 0.f, 0.f, 0.f};
            ldsm4t(q[0], qa); ldsm4t(a[0], ka); ldsm4t(q[1], qa + 512); ldsm4t(a[1], ka + 512);
            mma16(c0, a[0][0], a[0][1], a[0][2], a[0][3], q[0][0], q[0][1]);
            mma16(c1, a[0][0], a[0][1], a[0][2], a[0][3], q[0][2], q[0][3]);
            mma16(c0, a[1][0], a[1][1], a[1][2], a[1][3], q[1][0], q[1][1]);
            mma16(c1, a[1][0], a[1][1], a[1][2], a[1][3], q[1][2], q[1][3]);
            sts32f(sxw, c0[0] + c1[2]);
            sts32f(sxw + SMR * 4, c0[1] + c1[3]);
            if (s < NSEG - 1) bar_arrive(BAR_S, 320);
        }
        uint32_t qx[4][4];
        const uint32_t base = xs + ((c == 2 ? 0 : 2) + (m & 1)) * 2048 + ((w - 2) * 64 + 8 * (m >> 1) + r) * 16;
#pragma unroll
        for (int j = 0; j < 4; j++) ldsm4t(qx[j], base + j * 256);
        float c2[4] = {0.f, 0.f, 0.f, 0.f}, c3[4] = {0.f, 0.f, 0.f, 0.f};
#pragma unroll
        for (int j = 0; j < 2; j++) {
            mma16(c2, qx[2 * j][0], qx[2 * j][1], qx[2 * j][2], qx[2 * j][3], a[j][0], a[j][1]);
            mma16(c3, qx[2 * j + 1][0], qx[2 * j + 1][1], qx[2 * j + 1][2], qx[2 * j + 1][3], a[j][2], a[j][3]);
        }
        const uint32_t sxx = sb + SM_SXX + (g * SXR + 8 * (w - 2) + 2 * t) * 4;
        sts64f(sxx, c2[0] + c3[0], c2[1] + c3[1]);
        sts64f(sxx + 8 * SXR * 4, c2[2] + c3[2], c2[3] + c3[3]);
    }
    xrest(sb, xs, mb, c, h, s, w, lane, 1);
}

#define PAUSE_BOTH 0
#define VLATE 0
#define FENCE_EARLY 1
#define JOINT_GO 0
#define SHIP_AT 2
#define SHIP_DELAY 100
#define XN_AT 0
#define POLITE 0
#define W_PACE 1400
#define REGS_A 176
#define POLL_MODE 0
#define UMID 2
#define DELAY1 380
#define STAG1 200
#define DELAY2 280
#define STAG2 200
#define DELAY2N 1000

__device__ __forceinline__ void st_relaxed64(void* p, uint32_t lo, uint32_t hi) {
    asm volatile("{.reg .b64 v; mov.b64 v,{%1,%2}; st.relaxed.gpu.global.b64 [%0],v;}" ::"l"(p), "r"(lo), "r"(hi) : "memory");
}
__device__ __forceinline__ uint2 ld_relaxed64(const void* p) {
    uint2 v;
    asm volatile("{.reg .b64 v; ld.relaxed.gpu.global.b64 v,[%2]; mov.b64 {%0,%1},v;}" : "=r"(v.x), "=r"(v.y) : "l"(p) : "memory");
    return v;
}
__device__ __forceinline__ void sts32(uint32_t a, uint32_t v) { asm volatile("st.shared.u32 [%0],%1;" ::"r"(a), "r"(v) : "memory"); }

__global__ void __cluster_dims__(3, 1, 1) __launch_bounds__(384, 1)
k_chain(const __grid_constant__ CUtensorMap tmWq, const __grid_constant__ CUtensorMap tmWk, const __grid_constant__ CUtensorMap tmWv,
        const __grid_constant__ CUtensorMap tmWo, const __nv_bfloat16* __restrict__ x, const __nv_bfloat16* __restrict__ mem0,
        uint8_t* __restrict__ xb) {
    extern __shared__ __align__(1024) uint8_t smem[];
    const uint32_t sb = smem_u32(smem);
    const int tid = threadIdx.x, lane = tid & 31;
    const int warp = __shfl_sync(~0u, tid >> 5, 0);
    const int c = blockIdx.x % 3, h = blockIdx.x / 3;
    const uint32_t bar_qm = sb + SM_BAR, bar_x = sb + SM_BAR + 24, bar_xn = sb + SM_BAR + 48, bar_xf = sb + SM_BAR + 64, bar_w = sb + SM_BAR + 72;
    int dead = 0;

    pdl_launch();
    {
        if (tid == 0) {
            for (int i = 0; i < 11; i++) mbar_init(bar_qm + 8 * i, i < 3 ? 9 : (i == 8 ? 24 : 1));
            asm volatile("fence.mbarrier_init.release.cluster;" ::: "memory");
        }
        const int r0 = warp == 11 ? blockIdx.x : 96 + blockIdx.x * 11 + warp, r1 = warp == 11 ? SEQ : r0 + 1056;
        uint4 xr0[3], xr1[3];
        ln_load(xr0, x, r0, lane);
        ln_load(xr1, x, r1, lane);
        uint4 m0[5];
#pragma unroll
        for (int i = 0; i < 5; i++) {
            m0[i] = make_uint4(0, 0, 0, 0);
            if (warp >= 8 && tid - 256 + i * 128 < 576)
                asm volatile("ld.global.nc.v4.u32 {%0,%1,%2,%3},[%4];" : "=r"(m0[i].x), "=r"(m0[i].y), "=r"(m0[i].z), "=r"(m0[i].w)
                             : "l"(reinterpret_cast<const uint4*>(mem0) + tid - 256 + i * 128));
        }
        __syncthreads();
        if (warp == 8) PSTAMP(14);
        if (tid == 0) {
            asm volatile("{.reg .pred p; setp.eq.u32 p,%0,0x7fc1a5a5; @p nanosleep.u32 1;}" ::"r"(xr0[0].x ^ xr1[1].y) : "memory");
            mbar_expect_tx(bar_w + 8, 49152);
            for (int i = 0; i < 6; i++)
                tma2d(sb + (i < 4 ? SM_XN + i * 8192 : SM_TAB + (i - 4) * 8192), &tmWo, c * 192 + (i >> 1) * 64, h * DH + (i & 1) * 64, bar_w + 8);
            const CUtensorMap* tw = c == 0 ? &tmWq : (c == 1 ? &tmWk : &tmWv);
            mbar_expect_tx(bar_w, 147456);
            const uint32_t t0 = clk32();
            for (int i = 0; i < 6; i++) {
                while ((int)(clk32() - t0) < i * W_PACE);
                tma2d(sb + SM_STG_W + (i & 1) * 73728 + (i >> 1) * 24576, tw, h * DH + (i & 1) * 64, (i >> 1) * 192, bar_w);
            }
        }
        ln_row(xr0, r0, lane);
        if (warp == 11) {
            asm volatile("fence.acq_rel.gpu;" ::: "memory");
            __syncwarp();
            if (lane == 0) red_add1(g_tab + 100);
        }
        if (warp >= 8) {
#pragma unroll
            for (int i = 0; i < 5; i++) {
                const int ci = tid - 256 + i * 128;
                if (ci < 576) {
                    const uint32_t wv[4] = {m0[i].x, m0[i].y, m0[i].z, m0[i].w};
                    uint16_t* dst = reinterpret_cast<uint16_t*>(smem + SM_MEMT + (ci % 72) * 128 + (ci / 72) * 2);
#pragma unroll
                    for (int j = 0; j < 4; j++) { dst[16 * j] = (uint16_t)wv[j]; dst[16 * j + 8] = (uint16_t)(wv[j] >> 16); }
                }
            }
        }
        if (warp == 8) PSTAMP(15);
        if (r1 < SEQ) ln_row(xr1, r1, lane);
        if (warp < 8) {
            uint8_t* blk = xb + (size_t)blockIdx.x * 65536;
            uint8_t* c2b = xb + (size_t)96 * 65536;
            for (int i = tid; i < 1024; i += 256) *reinterpret_cast<uint4*>(blk + (i >> 9) * 32768 + (i & 511) * 16) = make_uint4(0, 0, 0, 0);
            if (tid < 48) {
                const int o = blockIdx.x * 96 + (tid % 6) * 16, v = tid / 6;
                *reinterpret_cast<uint4*>(c2b + (v >> 2) * 65536 + (v & 3) * 4096 + (o >> 12) * 16384 + (o & 4095)) = make_uint4(0, 0, 0, 0);
            } else if (tid < 60) {
                const int v = tid - 48;
                *reinterpret_cast<uint4*>((v < 4 ? blk : c2b + ((v >> 2) - 1) * 65536) + 0xE000 + ((v >> 1) & 1) * 4096 + (blockIdx.x & 31) * 128 + (v & 1) * 16) = make_uint4(0, 0, 0, 0);
            }
        }
        if (warp < 8) bar_arrive(BAR_QD, 384);
        PSTAMP(4);
    }
    auto ship_x = [&](int sl) {
        const uint32_t src = sb + SM_X + sl * 24576 + c * 8192, bx = bar_x + sl * 8;
        const uint32_t p1 = (c + 1) % 3, p2 = (c + 2) % 3;
        bulk_s2s(mapa(src, p1), src, 8192, mapa(bx, p1));
        bulk_s2s(mapa(src, p2), src, 8192, mapa(bx, p2));
        mbar_expect_tx(bx, 16384);
    };
    auto load_xn = [&](int seg) {
        const int b = seg & 1;
        mbar_expect_tx(bar_xn + 8 * b, XN_SEG_BYTES);
        bulk_g2s_mc(sb + SM_XN + b * XN_SEG_BYTES + c * 12288, g_xn + (size_t)seg * XN_SEG_BYTES + c * 12288, 12288, bar_xn + 8 * b, 7);
    };

    if (warp < 8) {
        if (REGS_A > 168) asm volatile("setmaxnreg.inc.sync.aligned.u32 %0;" ::"n"(REGS_A));
        mbar_wait(bar_w, 0, dead);
        PSTAMP(10);
        uint32_t W[NREG_K][4];
        {
            const int m = lane >> 3, r = lane & 7;
            const uint32_t wa = sb + SM_STG_W + (warp >> 2) * 73728 + (8 * (m >> 1) + r) * 128 + (((2 * (warp & 3) + (m & 1)) ^ r) << 4);
#pragma unroll
            for (int j = 0; j < 36; j++) {
                if (j < NREG_K) ldsm4t(W[j], wa + j * 2048);
                else {
                    uint32_t f[4];
                    ldsm4t(f, wa + j * 2048);
                    stsm4(sb + SM_WS + (j - NREG_K) * 4096 + (m >> 1) * 2048 + (2 * warp + (m & 1)) * 128 + r * 16, f[0], f[1], f[2], f[3]);
                }
            }
            fence_async();
        }
        bar_sync(BAR_A, 256);
        if (tid == 0) {
            int n = 0;
            while (ld_acquire1(g_tab + 100) < 96u) { if (++n > SPIN_LIMIT) { dead = 1; break; } }
            asm volatile("fence.proxy.async;" ::: "memory");
            mbar_expect_tx(bar_xn + 8, XN_SEG_BYTES);
            bulk_g2s(sb + SM_XN + XN_SEG_BYTES, g_xn + XN_SEG_BYTES, XN_SEG_BYTES, bar_xn + 8);
        }
        __syncwarp();
        asm volatile("barrier.cluster.arrive.relaxed.aligned;" ::: "memory");
        const uint32_t rb1 = mapa(sb, (c + 1) % 3), rb2 = mapa(sb, (c + 2) % 3);
        int slot = 0, ph3 = 0;
        for (int s = -2; s < NSEG; s++) {
            const int sl = slot == 2 ? 0 : slot + 1;
            int lane;
            asm volatile("mov.u32 %0,%%laneid;" : "=r"(lane));
            if (s >= 0) {
                uint32_t WS[36 - NREG_K][4];
                {
                    const uint32_t a = sb + SM_WS + ((lane >> 4) & 1) * 2048 + (2 * warp + ((lane >> 3) & 1)) * 128 + (lane & 7) * 16;
#pragma unroll
                    for (int j = 0; j < 36 - NREG_K; j++) ldsm4(WS[j], a + j * 4096);
                }
                const uint32_t doff = SM_MB + c * 2048 + warp * 256 + lane * 4 + sl * 6144;
                const uint32_t ma = sb + SM_MEMT + lane * 16;
                bar_sync(BAR_MEM, 384);
                float a0[4] = {0.f, 0.f, 0.f, 0.f}, a1[4] = {0.f, 0.f, 0.f, 0.f}, a2[4] = {0.f, 0.f, 0.f, 0.f};
                uint32_t b[5][4];
                constexpr int J0 = NREG_K / 2;
                ldsm4t(b[0], ma + J0 * 512);
                ldsm4t(b[1], ma + ((J0 + 1) % 18) * 512);
                TSTAMP(0);
#pragma unroll
                for (int jj = 0; jj < 18; jj++) {
                    const int j = (jj + J0) % 18;
                    if (jj == 1) { ldsm4t(b[2], ma + ((J0 + 2) % 18) * 512); ldsm4t(b[3], ma + ((J0 + 3) % 18) * 512); }
                    if (jj >= 1 && jj + 3 < 18) ldsm4t(b[(jj + 3) % 5], ma + ((jj + 3 + J0) % 18) * 512);
                    const uint32_t(&bb)[4] = b[jj % 5];
                    float(&c0)[4] = (2 * jj) % 3 == 0 ? a0 : ((2 * jj) % 3 == 1 ? a1 : a2);
                    float(&c1)[4] = (2 * jj + 1) % 3 == 0 ? a0 : ((2 * jj + 1) % 3 == 1 ? a1 : a2);
                    if (2 * j < NREG_K) mma16(c0, W[2 * j][0], W[2 * j][1], W[2 * j][2], W[2 * j][3], bb[0], bb[1]);
                    else mma16(c0, WS[2 * j - NREG_K][0], WS[2 * j - NREG_K][1], WS[2 * j - NREG_K][2], WS[2 * j - NREG_K][3], bb[0], bb[1]);
                    if (2 * j + 1 < NREG_K) mma16(c1, W[2 * j + 1][0], W[2 * j + 1][1], W[2 * j + 1][2], W[2 * j + 1][3], bb[2], bb[3]);
                    else mma16(c1, WS[2 * j + 1 - NREG_K][0], WS[2 * j + 1 - NREG_K][1], WS[2 * j + 1 - NREG_K][2], WS[2 * j + 1 - NREG_K][3], bb[2], bb[3]);
                }
                const uint32_t w0 = pack_bf16(a0[0] + a1[0] + a2[0], a0[1] + a1[1] + a2[1]);
                const uint32_t w1 = pack_bf16(a0[2] + a1[2] + a2[2], a0[3] + a1[3] + a2[3]);
                const uint32_t boff = SM_BAR + sl * 8;
                st_async32(rb1 + doff, w0, rb1 + boff); st_async32(rb2 + doff, w0, rb2 + boff);
                st_async32(rb1 + doff + 128, w1, rb1 + boff); st_async32(rb2 + doff + 128, w1, rb2 + boff);
                sts32(sb + doff, w0); sts32(sb + doff + 128, w1);
                __syncwarp();
                if (lane == 0) mbar_arrive(sb + boff);
                if (!FENCE_EARLY) fence_async();
                if (s < NSEG - 1) bar_arrive(BAR_U, 384);
                TSTAMP(1);
            }
            const int sn = s + 2;
            const bool bulk = sn < NSEG;
            const uint64_t desc0 = mk_desc(sb + SM_XN + (sn & 1) * XN_SEG_BYTES, 16, 1024);
            const uint64_t da = (uint64_t)(((sb + SM_WS + (warp >> 2) * 1024) & 0x3FFFF) >> 4) | (128ull << 16) | (8ull << 32);
            float acc[16];
            if (s >= 0) {
                mbar_wait(bar_x + sl * 8, ph3, dead);
                const uint32_t xs = sb + SM_X + sl * 24576, mb = sb + SM_MB + sl * 6144;
                if (warp < 4) {
                    if (s == NSEG - 1) {
                        if (c == 2) xrest(sb, xs, mb, c, h, s, warp, lane, 0);
                        bar_arrive(BAR_GO, 256);
                        break;
                    }
                    const uint4 at = lds128(sb + SM_AUX + (warp * 32 + lane) * 16);
                    const uint32_t qa = mb + at.y, sxw = at.z;
                    uint32_t kf[4][4];
#pragma unroll
                    for (int j = 0; j < 4; j++) ldsm4t(kf[j], xs + at.w + j * 256);
                    mbar_wait(bar_qm + sl * 8, ph3, dead);
                    uint32_t q[2][4];
                    ldsm4t(q[0], qa); ldsm4t(q[1], qa + 512);
                    float c0[4] = {0.f, 0.f, 0.f, 0.f}, c1[4] = {0.f, 0.f, 0.f, 0.f}, c2[4] = {0.f, 0.f, 0.f, 0.f}, c3[4] = {0.f, 0.f, 0.f, 0.f};
                    mma16(c0, kf[0][0], kf[0][1], kf[0][2], kf[0][3], q[0][0], q[0][1]);
                    mma16(c1, kf[1][0], kf[1][1], kf[1][2], kf[1][3], q[0][2], q[0][3]);
                    mma16(c2, kf[2][0], kf[2][1], kf[2][2], kf[2][3], q[1][0], q[1][1]);
                    mma16(c3, kf[3][0], kf[3][1], kf[3][2], kf[3][3], q[1][2], q[1][3]);
                    sts32f(sxw, (c0[0] + c1[0]) + (c2[0] + c3[0]));
                    sts32f(sxw + SMR * 4, (c0[1] + c1[1]) + (c2[1] + c3[1]));
                    sts32f(sxw + 64, (c0[2] + c1[2]) + (c2[2] + c3[2]));
                    sts32f(sxw + SMR * 4 + 64, (c0[3] + c1[3]) + (c2[3] + c3[3]));
                    bar_arrive(BAR_S, 320);
                    TSTAMP(2);
                    __syncwarp();
                    if (c == 2) xrest(sb, xs, mb, c, h, s, warp, lane, 0);
                    TSTAMP(5);
                    bar_sync(BAR_GO, JOINT_GO ? 384 : 256);
                } else {
                    xattn(sb, xs, mb, bar_qm + sl * 8, ph3, c, h, s, warp - 4, lane, dead);
                    TSTAMP(2);
                    if (s == NSEG - 1) {
                        bar_sync(BAR_GO, 256);
                        if (tid == 128) { asm volatile("fence.acq_rel.gpu;" ::: "memory"); red_add1(g_flag + 15 * 32 + FL_OX); }
                        break;
                    }
                    if (JOINT_GO) bar_sync(BAR_GO, 384); else bar_sync(BAR_GO2, 256);
                }
            }
#pragma unroll
            for (int i = 0; i < 16; i++) acc[i] = 0.f;
            if (bulk) {
                mbar_wait(bar_xn + (sn & 1) * 8, (sn >> 1) & 1, dead);
                wg_fence();
#pragma unroll
                for (int j = 0; j < BULK1; j++) {
                    wgmma_n32_rs(acc, W[j], desc0 + (uint64_t)(((j >> 2) * 4096 + (j & 3) * 32) >> 4), j > 0);
                    if (j >= BULK1 - POLITE - 1 && j < BULK1 - 1) { wg_commit(); wg_wait<0>(); wg_fence(); }
                }
                wg_commit();
                wg_wait<0>();
            }
            if (s >= 0 && (s & 3) == 3) bar_arrive(BAR_OX, 288);
            if (s >= 0) bar_sync(BAR_QD, 320);
            if (bulk) {
                wg_fence();
#pragma unroll
                for (int j = BULK1; j < NREG_K; j++) wgmma_n32_rs(acc, W[j], desc0 + (uint64_t)(((j >> 2) * 4096 + (j & 3) * 32) >> 4), j > 0);
#pragma unroll
                for (int j = NREG_K; j < 36; j++)
                    wgmma_n32_ss(acc, da + (uint64_t)((j - NREG_K) * 256), desc0 + (uint64_t)(((j >> 2) * 4096 + (j & 3) * 32) >> 4));
                wg_commit();
                wg_wait<0>();
            }
            if (s > -2 && lane < 3)
                asm volatile("mbarrier.arrive.relaxed.cluster.shared::cluster.b64 _,[%0];" ::"r"(mapa(bar_xf, lane)) : "memory");
            TSTAMP(3);
            if (bulk) {
                const uint32_t xo = sb + SM_X + slot * 24576 + c * 8192 + ((lane >> 4) & 1) * 2048 + (16 * warp + 8 * ((lane >> 3) & 1) + (lane & 7)) * 16;
                stsm4(xo, pack_bf16(acc[0], acc[1]), pack_bf16(acc[2], acc[3]), pack_bf16(acc[4], acc[5]), pack_bf16(acc[6], acc[7]));
                stsm4(xo + 4096, pack_bf16(acc[8], acc[9]), pack_bf16(acc[10], acc[11]), pack_bf16(acc[12], acc[13]), pack_bf16(acc[14], acc[15]));
                if (FENCE_EARLY || s == -2) fence_async();
            }
            if (s == -2) {
                asm volatile("barrier.cluster.wait.acquire.aligned;" ::: "memory");
                bar_arrive(0, 288);
            }
            TSTAMP(4);
            if (s >= 0) { TFLUSH(); }
            if (sl == 2 && s >= 0) ph3 ^= 1;
            slot = sl;
        }
        cluster_sync();
    } else {
        if (REGS_A > 168) asm volatile("setmaxnreg.dec.sync.aligned.u32 %0;" ::"n"(504 - 2 * REGS_A));
        const int w = warp - 8, bt = tid - 256;
        const int cta = blockIdx.x;
        uint8_t* const c2b = xb + (size_t)96 * 65536;
        PSTAMP(11);
        asm volatile("barrier.cluster.arrive.relaxed.aligned;" ::: "memory");
        PSTAMP(12);
        PSTAMP(13);
        volatile uint32_t* sp = reinterpret_cast<volatile uint32_t*>(smem + SM_TIM + 900);
        if (bt == 32) sp[1] = near_parity(xb + (size_t)cta * 65536, cta);
        __syncwarp();
        mbar_wait(bar_w + 8, 0, dead);
        PSTAMP(6);
        uint32_t WO[3][8][4];
        {
            const int m = lane >> 3, r = lane & 7;
#pragma unroll
            for (int i = 0; i < 3; i++)
#pragma unroll
                for (int j = 0; j < 8; j++) {
                    const int k = 16 * j + 8 * (m >> 1) + r, ch = 2 * (3 * w + i) + (m & 1);
                    ldsm4t(WO[i][j], sb + (ch < 16 ? SM_XN + (ch >> 3) * 16384 : SM_TAB) + k * 128 + (((ch & 7) ^ r) << 4));
                }
        }
        bar_sync(BAR_QD, 384);
        {
            const int g = lane >> 2, t = lane & 3, m = lane >> 3, r = lane & 7;
            sts128(sb + SM_AUX + bt * 16, make_uint4(0, (w & 1) * 1024 + lane * 16,
                   sb + SM_SX + (2 * t * SMR + (1 + (w & 2)) * 16 + (g >> 1) * 4 + (w & 1) * 2 + (g & 1)) * 4,
                   8192 + ((w & 2) + (m & 1)) * 2048 + ((w & 1) * 64 + 8 * (m >> 1) + r) * 16));
            sts128(sb + SM_AUX + 2048 + bt * 16, make_uint4(0, (w & 1) * 1024 + ((((m & 1) << 1) | (m >> 1)) * 8 + r) * 16,
                   sb + SM_SX + (2 * t * SMR + (g >> 1) * 4 + (w & 1) * 2 + (g & 1)) * 4, 2048 + (w & 1) * 1024 + lane * 16));
        }
        bar_arrive(BAR_MEM, 384);
        if (lane == 0) {
            if (w == 0) {
                int n = 0;
                while (ld_acquire1(g_tab + 100) < 96u) { if (++n > SPIN_LIMIT) { dead = 1; break; } }
                asm volatile("fence.proxy.async;" ::: "memory");
                mbar_expect_tx(bar_xn, XN_SEG_BYTES);
                bulk_g2s(sb + SM_XN, g_xn, XN_SEG_BYTES, bar_xn);
            } else if (w == 1) {
                asm volatile("fence.acq_rel.gpu;" ::: "memory");
                st_relaxed1(g_tab + cta, 1u + sp[1]);
            } else sp[w] = near_parity(c2b + (w - 2) * 65536, cta);
        }
        __syncwarp();
        PSTAMP(7);
        asm volatile("barrier.cluster.wait.acquire.aligned;" ::: "memory");
        if (w == 0) {
            bar_sync(0, 288);
            PSTAMP(9);
            if (lane == 0) {
                asm volatile("fence.proxy.async;" ::: "memory");
                ship_x(0);
                mbar_wait(bar_x, 0, dead);
                load_xn(2);
            }
        } else {
            uint32_t tv;
            int n = 0;
            while ((tv = ld_acquire1(g_tab + bt - 32)) == 0u) { if (++n > SPIN_LIMIT) { dead = 1; break; } }
            reinterpret_cast<volatile uint8_t*>(smem + SM_TIM + 800)[bt - 32] = (uint8_t)(tv - 1);
        }
        dead = __any_sync(~0u, dead);
        bar_sync(BAR_B, 128);
        const uint32_t pinfo = __shfl_sync(~0u, sp[2] | (sp[3] << 1) | (sp[1] << 2), 0);
        if (bt == 0) asm volatile("fence.proxy.async;" ::: "memory");
        PSTAMP(5);
        for (int i = 0; i < 3; i++) {
            const int u = (c * 12 + w * 3 + i) * 4 + (lane >> 3), d = u < 96 ? u : 2 * (u - 96);
            reinterpret_cast<volatile uint32_t*>(smem + SM_TAB)[bt * 4 + i] =
                d * 65536 + (reinterpret_cast<volatile uint8_t*>(smem + SM_TIM + 800)[d] & 1) * 4096 + (u < 96 ? 0 : 2048) + h * 64 + (lane & 7) * 8;
        }
        reinterpret_cast<volatile uint32_t*>(smem + SM_TAB)[bt * 4 + 3] = sb + SM_SX + ((lane >> 2) * SMR + 4 * (lane & 3)) * 4;
        PSTAMP(8);
        __syncwarp();
        const float sc = 0.08838834764831845f * 1.4426950408889634f;
        int slot = 0, ph3 = 0;
        for (int s = 0; s < NSEG; s++) {
            int lane;
            asm volatile("mov.u32 %0,%%laneid;" : "=r"(lane));
            const int g = lane >> 2, t = lane & 3, m = lane >> 3, r = lane & 7, bt = w * 32 + lane;
            const uint32_t xs = sb + SM_X + slot * 24576;
            const uint32_t mb = sb + SM_MB + slot * 6144;
            if (bt == 64) mbar_expect_tx(bar_qm + slot * 8, 4096);
            if (s == NSEG - 1) break;
            const uint32_t tag = ((s >> 1) & 1) ^ 1;
            const uint4 tab = lds128(sb + SM_TAB + bt * 16);
            const uint32_t sxr = tab.w;
            const uint32_t l16 = sb + lane * 16;
            const uint32_t one = 0x3f803f80u;
            uint32_t va[2][2][4], vmm[4];
            mbar_wait(bar_x + slot * 8, ph3, dead);
            if (XN_AT > 0 && bt == 32 && s + 3 < NSEG) {
                const uint32_t t0 = clk32();
                mbar_wait(bar_xf, s & 1, dead);
                while ((int)(clk32() - t0) < XN_AT);
                load_xn(s + 3);
            }
            __syncwarp();
            bar_sync(BAR_U, 384);
            if (XN_AT == 0 && bt == 32 && s + 3 < NSEG) {
                mbar_wait(bar_xf, s & 1, dead);
                load_xn(s + 3);
            }
            __syncwarp();
            const uint32_t vaa = xs + 16384 + (m >> 1) * 2048 + (32 * w + 8 * (m & 1) + r) * 16;
            ldsm4(va[0][0], vaa); ldsm4(va[1][0], vaa + 256);
            ldsm4(va[0][1], vaa + 4096); ldsm4(va[1][1], vaa + 4096 + 256);
            TSTAMP(1);
            mbar_wait(bar_qm + slot * 8, ph3, dead);
            ldsm4(vmm, mb + 4096 + bt * 16);
            TSTAMP(2);
            bar_sync(BAR_S, 320);
            float2 v[5];
            {
                uint4 u[5];
#pragma unroll
                for (int b = 0; b < 5; b++) u[b] = lds128(sxr + b * 64);
#pragma unroll
                for (int b = 0; b < 5; b++) v[b] = make_float2(__uint_as_float(u[b].x) + __uint_as_float(u[b].z), __uint_as_float(u[b].y) + __uint_as_float(u[b].w));
            }
            TSTAMP(3);
            float mx = fmaxf(fmaxf(fmaxf(v[4].x, v[4].y), fmaxf(v[1].x, v[1].y)), fmaxf(fmaxf(v[2].x, v[2].y), fmaxf(v[3].x, v[3].y)));
            mx = fmaxf(mx, fmaxf(v[0].x, v[0].y));
            mx = fmaxf(mx, __shfl_xor_sync(~0u, mx, 1));
            mx = fmaxf(mx, __shfl_xor_sync(~0u, mx, 2));
            mx *= sc;
            float o[2][4] = {{0.f, 0.f, 0.f, 0.f}, {0.f, 0.f, 0.f, 0.f}}, rs[4] = {0.f, 0.f, 0.f, 0.f};
            {
                uint32_t pk[5];
#pragma unroll
                for (int b = 0; b < 5; b++) pk[b] = pack_bf16(ex2(fmaf(v[b].x, sc, -mx)), ex2(fmaf(v[b].y, sc, -mx)));
                mma8(o[0], vmm[0], vmm[1], pk[0]);
                mma8(o[1], vmm[2], vmm[3], pk[0]);
                mma8(rs, one, one, pk[0]);
                mma16(o[0], va[0][0][0], va[0][0][1], va[0][0][2], va[0][0][3], pk[1], pk[2]);
                mma16(o[1], va[1][0][0], va[1][0][1], va[1][0][2], va[1][0][3], pk[1], pk[2]);
                mma16(rs, one, one, one, one, pk[1], pk[2]);
                mma16(o[0], va[0][1][0], va[0][1][1], va[0][1][2], va[0][1][3], pk[3], pk[4]);
                mma16(o[1], va[1][1][0], va[1][1][1], va[1][1][2], va[1][1][3], pk[3], pk[4]);
                mma16(rs, one, one, one, one, pk[3], pk[4]);
                stsm4(l16 + SM_OT + w * 512, pack_bf16(o[0][0], o[0][1]), pack_bf16(o[0][2], o[0][3]), pack_bf16(o[1][0], o[1][1]), pack_bf16(o[1][2], o[1][3]));
                TSTAMP(4);
                bar_sync(BAR_B, 128);
            }
            uint32_t ob[4][4];
#pragma unroll
            for (int j = 0; j < 4; j++) ldsm4t(ob[j], l16 + SM_OT + j * 512);
            TSTAMP(5);
            {
                float d[3][2][4];
#pragma unroll
                for (int i = 0; i < 3; i++)
#pragma unroll
                    for (int k = 0; k < 4; k++) d[i][0][k] = d[i][1][k] = 0.f;
#pragma unroll
                for (int j = 0; j < 8; j++)
#pragma unroll
                    for (int i = 0; i < 3; i++)
                        mma16(d[i][j & 1], WO[i][j][0], WO[i][j][1], WO[i][j][2], WO[i][j][3], ob[j >> 1][(j & 1) * 2], ob[j >> 1][(j & 1) * 2 + 1]);
                const float i0 = rcp_fast(rs[0]), i1 = rcp_fast(rs[1]);
                uint8_t* const xs1 = xb + (s & 1) * 32768;
                const uint32_t off[3] = {tab.x, tab.y, tab.z};
#pragma unroll
                for (int i = 0; i < 3; i++)
                    st_relaxed64(xs1 + off[i], settag(__uint_as_float(pack_bf16((d[i][0][0] + d[i][1][0]) * i0, (d[i][0][1] + d[i][1][1]) * i1)), tag),
                                 pack_bf16((d[i][0][2] + d[i][1][2]) * i0, (d[i][0][3] + d[i][1][3]) * i1));
            }
            const uint32_t t_st = clk32();
            TSTAMP(6);
            const bool owner = w == 0 || (w == 1 && !(cta & 1));
            const uint8_t* src = xb + (cta * 65536 + (pinfo & 4u) * 1024 + (s & 1) * 32768 + (w & 1) * 2048) + (uint32_t)(t * 64 + g * 8);
            if (JOINT_GO) bar_arrive(BAR_GO, 384);
            else { bar_arrive(BAR_GO, 256); bar_arrive(BAR_GO2, 256); }
            if (w == 2) while ((int)(clk32() - t_st) < SHIP_DELAY);
            if (bt == 64) {
                ship_x(slot == 2 ? 0 : slot + 1);
            }
            __syncwarp();
            const uint8_t* src2 = c2b + (((s >> 1) & 1) * 65536 + ((s & 1) * 0x3000 ^ (((pinfo >> ((s >> 1) & 1)) & 1) << 12))) + (uint32_t)(bt * 16);
            const uint32_t mt = sb + SM_MEMT + bt * 16;
            uint32_t t_pub = 0;
            if (owner) {
                const int u = w == 0 ? cta : 96 + (cta >> 1), o = (u >> 2) * 256 + (u & 3) * 32;
                const uint32_t o_pub = (o >> 12) * 16384 + (o & 4095) + (t & 1) * 128 + g * 4 + (t >> 1) * 0x1000;
                const uint32_t msk = tag ^ 1u;
                int n = 0;
                uint2 v2[8];
                while ((int)(clk32() - t_st) < DELAY1);
#pragma unroll
                for (int i = 0; i < 8; i++) v2[i] = ld_relaxed64(src + i * 256);
                TSTAMP(7);
                const uint32_t sel = (g & 1) ? 0x3f800000u : 0x00003f80u;
                uint8_t* const pub = c2b + (((s >> 1) & 1) * 65536 + (s & 1) * 0x2000) + o_pub;
                while (!__all_sync(~0u, (and3(xand(v2[0].x, v2[1].x, msk), xand(v2[2].x, v2[3].x, msk), xand(v2[4].x, v2[5].x, msk) & xand(v2[6].x, v2[7].x, msk)) | dead) & 1u)) {
#pragma unroll
                    for (int i = 0; i < 8; i++) if (!((v2[i].x ^ msk) & 1u)) v2[i] = ld_relaxed64(src + i * 256);
                    if (++n > SPIN_LIMIT) dead = 1;
                }
                float r0[4] = {0.f, 0.f, 0.f, 0.f}, r1[4] = {0.f, 0.f, 0.f, 0.f}, r2[4] = {0.f, 0.f, 0.f, 0.f}, r3[4] = {0.f, 0.f, 0.f, 0.f};
                mma16(r0, v2[0].x, v2[0].y, v2[1].x, v2[1].y, sel, sel);
                mma16(r1, v2[2].x, v2[2].y, v2[3].x, v2[3].y, sel, sel);
                mma16(r2, v2[4].x, v2[4].y, v2[5].x, v2[5].y, sel, sel);
                mma16(r3, v2[6].x, v2[6].y, v2[7].x, v2[7].y, sel, sel);
                uint32_t word = (t & 1) ? pack_bf16((r0[2] + r1[2]) + (r2[2] + r3[2]), (r0[3] + r1[3]) + (r2[3] + r3[3]))
                                        : pack_bf16((r0[0] + r1[0]) + (r2[0] + r3[0]), (r0[1] + r1[1]) + (r2[1] + r3[1]));
                if (word == 0u) word = 0x80000000u;
                st_relaxed1(pub, word);
                t_pub = clk32();
                st_relaxed1(c2b + ((((s - 1) >> 1) & 1) * 65536 + ((s - 1) & 1) * 0x2000) + o_pub, 0u);
            }
            if (w < 2) bar_arrive(BAR_QD, 320);
            {
                bar_sync(BAR_B, 128);
                asm volatile("{.reg .pred p; .reg .u32 x; ld.shared.u32 x,[%1]; setp.ne.u32 p,x,0x7fc1a5a5; @p mov.u32 %0,%%clock;}" : "+r"(t_pub) : "r"(sb + SM_TAB) : "memory");
            }
            TSTAMP(8);
            {
                uint4 v4[5];
                uint32_t ok[5];
                v4[4] = make_uint4(1, 1, 1, 1);
                while ((int)(clk32() - t_pub) < DELAY2);
#pragma unroll
                for (int i = 0; i < 4; i++) v4[i] = ld_relaxed4(src2 + (i & 1) * 2048 + (i >> 1) * 16384);
                if (w >= 2) v4[4] = ld_relaxed4(src2 + 32768 - 1024);
                int n = 0;
                while (true) {
#pragma unroll
                    for (int i = 0; i < 4; i++) sts128(mt + i * 2048, v4[i]);
                    if (w >= 2) sts128(mt + 8192 - 1024, v4[4]);
#pragma unroll
                    for (int i = 0; i < 5; i++) ok[i] = min(__vimin3_u32(v4[i].x, v4[i].y, v4[i].z), v4[i].w);
                    const uint32_t all = min(__vimin3_u32(ok[0], ok[1], ok[2]), min(ok[3], ok[4]));
                    if (__all_sync(~0u, (all | dead) != 0)) break;
#pragma unroll
                    for (int i = 0; i < 5; i++) if (!ok[i]) v4[i] = ld_relaxed4(src2 + (i & 1) * 2048 + (i >> 1) * 16384 - (i == 4 ? 1024 : 0));
                    if (++n > SPIN_LIMIT) dead = 1;
                }
                bar_arrive(BAR_MEM, 384);
            }
            TSTAMP(9);
            if (w == 3 && (s & 3) == 3) {
                bar_sync(BAR_OX, 288);
                asm volatile("fence.acq_rel.gpu;" ::: "memory");
                if (lane == 0) red_add1(g_flag + (s >> 2) * 32 + FL_OX);
            }
            TSTAMP(10);
            TFLUSH();
            if (slot == 2) { slot = 0; ph3 ^= 1; } else slot++;
        }
        if (bt == 0) { g_tab[cta] = 0u; if (cta == 0) g_tab[100] = 0u; }
        cluster_sync();
    }
}

constexpr int G_ST = 4;
constexpr int G_STAGE = 16384 + 24576;
constexpr int T_STG = G_ST * G_STAGE;
constexpr int AUXB = 3072 + 1536;
constexpr int T_AUX0 = T_STG + 49152;
constexpr int T_B2 = T_AUX0 + 2 * AUXB;
constexpr int T_BAR = T_B2 + 2304;
constexpr int T_SMEM = T_BAR + 256 + 1024;
static_assert(T_SMEM <= 232448, "smem");
constexpr int NINIT = 36;
#define KW2 12
#define KW4 14
#define KF2 8
#define KF4 12
#define SCHED_AHEAD 1
#define WG_LAG 0
#define DEDICATED 0
#define DED0 36
#define KSW_S 8
#define KSF_S 9
#define T_START_DELAY 18000
#define RB_SMALL 15
__host__ __device__ constexpr bool small_rb(int rb) { return rb >= RB_SMALL; }
__host__ __device__ constexpr int ks_w(int rb) { return small_rb(rb) ? KSW_S : (rb == 0 ? 8 : (rb < KW2 ? 2 : (rb < KW4 ? 4 : 8))); }
__host__ __device__ constexpr int ks_f(int rb) { return small_rb(rb) ? KSF_S : (rb < KF2 ? 2 : (rb < KF4 ? 4 : 8)); }
__host__ __device__ constexpr int ntile(int rb) { return small_rb(rb) ? 9 : 3; }
__host__ __device__ constexpr int kpart(int total, int ks) { return ks == 2 ? total / 2 - 4 : (ks == 4 ? total / 4 - 2 : (ks == 1 ? total : (ks <= 9 ? total / ks - 1 : total / ks))); }

__device__ __forceinline__ void wgmma_ss(float (&d)[32], uint64_t da, uint64_t db, int scale_d) {
    asm volatile("{.reg .pred p; setp.ne.b32 p,%34,0;\n"
                 "wgmma.mma_async.sync.aligned.m64n64k16.f32.bf16.bf16 {"
                 "%0,%1,%2,%3,%4,%5,%6,%7,%8,%9,%10,%11,%12,%13,%14,%15,%16,%17,%18,%19,%20,%21,%22,%23,"
                 "%24,%25,%26,%27,%28,%29,%30,%31},%32,%33,p,1,1,0,1;}"
                 : "+f"(d[0]), "+f"(d[1]), "+f"(d[2]), "+f"(d[3]), "+f"(d[4]), "+f"(d[5]), "+f"(d[6]), "+f"(d[7]),
                   "+f"(d[8]), "+f"(d[9]), "+f"(d[10]), "+f"(d[11]), "+f"(d[12]), "+f"(d[13]), "+f"(d[14]), "+f"(d[15]),
                   "+f"(d[16]), "+f"(d[17]), "+f"(d[18]), "+f"(d[19]), "+f"(d[20]), "+f"(d[21]), "+f"(d[22]), "+f"(d[23]),
                   "+f"(d[24]), "+f"(d[25]), "+f"(d[26]), "+f"(d[27]), "+f"(d[28]), "+f"(d[29]), "+f"(d[30]), "+f"(d[31])
                 : "l"(da), "l"(db), "r"(scale_d));
}
__device__ __forceinline__ void wgmma_ss(float (&d)[96], uint64_t da, uint64_t db, int scale_d) {
    asm volatile("{.reg .pred p; setp.ne.b32 p,%98,0;\n"
                 "wgmma.mma_async.sync.aligned.m64n192k16.f32.bf16.bf16 {"
                 "%0,%1,%2,%3,%4,%5,%6,%7,%8,%9,%10,%11,%12,%13,%14,%15,%16,%17,%18,%19,%20,%21,%22,%23,"
                 "%24,%25,%26,%27,%28,%29,%30,%31,%32,%33,%34,%35,%36,%37,%38,%39,%40,%41,%42,%43,%44,%45,%46,%47,"
                 "%48,%49,%50,%51,%52,%53,%54,%55,%56,%57,%58,%59,%60,%61,%62,%63,%64,%65,%66,%67,%68,%69,%70,%71,"
                 "%72,%73,%74,%75,%76,%77,%78,%79,%80,%81,%82,%83,%84,%85,%86,%87,%88,%89,%90,%91,%92,%93,%94,%95},"
                 "%96,%97,p,1,1,0,1;}"
                 : "+f"(d[0]), "+f"(d[1]), "+f"(d[2]), "+f"(d[3]), "+f"(d[4]), "+f"(d[5]), "+f"(d[6]), "+f"(d[7]),
                   "+f"(d[8]), "+f"(d[9]), "+f"(d[10]), "+f"(d[11]), "+f"(d[12]), "+f"(d[13]), "+f"(d[14]), "+f"(d[15]),
                   "+f"(d[16]), "+f"(d[17]), "+f"(d[18]), "+f"(d[19]), "+f"(d[20]), "+f"(d[21]), "+f"(d[22]), "+f"(d[23]),
                   "+f"(d[24]), "+f"(d[25]), "+f"(d[26]), "+f"(d[27]), "+f"(d[28]), "+f"(d[29]), "+f"(d[30]), "+f"(d[31]),
                   "+f"(d[32]), "+f"(d[33]), "+f"(d[34]), "+f"(d[35]), "+f"(d[36]), "+f"(d[37]), "+f"(d[38]), "+f"(d[39]),
                   "+f"(d[40]), "+f"(d[41]), "+f"(d[42]), "+f"(d[43]), "+f"(d[44]), "+f"(d[45]), "+f"(d[46]), "+f"(d[47]),
                   "+f"(d[48]), "+f"(d[49]), "+f"(d[50]), "+f"(d[51]), "+f"(d[52]), "+f"(d[53]), "+f"(d[54]), "+f"(d[55]),
                   "+f"(d[56]), "+f"(d[57]), "+f"(d[58]), "+f"(d[59]), "+f"(d[60]), "+f"(d[61]), "+f"(d[62]), "+f"(d[63]),
                   "+f"(d[64]), "+f"(d[65]), "+f"(d[66]), "+f"(d[67]), "+f"(d[68]), "+f"(d[69]), "+f"(d[70]), "+f"(d[71]),
                   "+f"(d[72]), "+f"(d[73]), "+f"(d[74]), "+f"(d[75]), "+f"(d[76]), "+f"(d[77]), "+f"(d[78]), "+f"(d[79]),
                   "+f"(d[80]), "+f"(d[81]), "+f"(d[82]), "+f"(d[83]), "+f"(d[84]), "+f"(d[85]), "+f"(d[86]), "+f"(d[87]),
                   "+f"(d[88]), "+f"(d[89]), "+f"(d[90]), "+f"(d[91]), "+f"(d[92]), "+f"(d[93]), "+f"(d[94]), "+f"(d[95])
                 : "l"(da), "l"(db), "r"(scale_d));
}
__device__ __forceinline__ float gelu_tanh(float hx) {
    const float u = hx * fmaf(hx * hx, 8.f * 0.7978845608028654f * 0.044715f, 2.f * 0.7978845608028654f);
    float th;
    asm("tanh.approx.f32 %0,%1;" : "=f"(th) : "f"(u));
    return fmaf(hx, th, hx);
}
__device__ __forceinline__ float2 ldbf2(const __nv_bfloat16* p) {
    uint32_t w = *reinterpret_cast<const uint32_t*>(p);
    return make_float2(__uint_as_float(w << 16), __uint_as_float(w & 0xffff0000u));
}

__device__ __forceinline__ void bulk_s2g(void* dst, uint32_t src, uint32_t bytes) {
    asm volatile("cp.async.bulk.global.shared::cta.bulk_group [%0],[%1],%2;" ::"l"(dst), "r"(src), "r"(bytes) : "memory");
}

__device__ __forceinline__ void tma2d_store(const CUtensorMap* tm, uint32_t src, int c0, int c1) {
    asm volatile("cp.async.bulk.tensor.2d.global.shared::cta.bulk_group [%0,{%2,%3}],[%1];" ::"l"(tm), "r"(src), "r"(c0), "r"(c1) : "memory");
}
__device__ __forceinline__ float4 lds128f(uint32_t a) {
    float4 v; asm volatile("ld.shared.v4.f32 {%0,%1,%2,%3},[%4];" : "=f"(v.x), "=f"(v.y), "=f"(v.z), "=f"(v.w) : "r"(a) : "memory");
    return v;
}

constexpr int TB_FULL = 0, TB_EMPTY = 32, TB_SFULL = 64, TB_SEMPTY = 72, TB_TQF = 80, TB_TQE = 96, TB_ORD = 112, TB_SQF = 128, TB_SQE = 136, TB_DATA = 160;

__device__ __forceinline__ float4 ldsc128f(uint32_t a) {
    float4 v; asm("ld.shared.v4.f32 {%0,%1,%2,%3},[%4];" : "=f"(v.x), "=f"(v.y), "=f"(v.z), "=f"(v.w) : "r"(a)); return v;
}
__device__ __forceinline__ float2 ldsc64f(uint32_t a) { float2 v; asm("ld.shared.v2.f32 {%0,%1},[%2];" : "=f"(v.x), "=f"(v.y) : "r"(a)); return v; }
__device__ __forceinline__ void stsm4n(uint32_t a, uint32_t r0, uint32_t r1, uint32_t r2, uint32_t r3) {
    asm volatile("stmatrix.sync.aligned.m8n8.x4.shared.b16 [%0],{%1,%2,%3,%4};" ::"r"(a), "r"(r0), "r"(r1), "r"(r2), "r"(r3));
}
__device__ __forceinline__ void store_acquire(uint32_t tb, uint32_t seq, int& dead) {
    int n = dead ? (SPIN_LIMIT << 4) : 0;
    while (true) {
        uint32_t c;
        asm volatile("ld.volatile.shared.u32 %0,[%1];" : "=r"(c) : "r"(tb + TB_SEMPTY) : "memory");
        if (c >= seq) break;
        if (++n > (SPIN_LIMIT << 4)) { dead = 1; break; }
    }
}
__device__ __forceinline__ void ln_stats(uint32_t st, int nt, float cnt, float& mean, float& rstd) {
    float m = 0.f, m2 = 0.f;
    for (int i = 0; i < nt; i++) m += lds64f(st + i * 1024).x;
    m *= 1.f / nt;
    for (int i = 0; i < nt; i++) { const float2 v = lds64f(st + i * 1024); m2 += v.y + cnt * (v.x - m) * (v.x - m); }
    mean = m; rstd = rsqrtf(m2 * (1.f / DM) + 1e-5f);
}

template <int NB>
__device__ __forceinline__ void tail_task(uint32_t sb, volatile int* store_task, int task, uint32_t it, uint32_t seq, int tid, int& dead) {
    constexpr int NJ = 8 * NB, BN = 64 * NB;
    const uint32_t tb = sb + T_BAR;
    const int lane = tid & 31, t = lane & 3, lr = (tid >> 5) * 16 + (lane >> 2);
    const uint32_t mrow = ((tid >> 5) * 16 + ((lane >> 3) & 1) * 8 + (lane & 7)) * 128, mchk = lane >> 4, mxor = lane & 7;
    const int type = task & 3, rb = (task >> 2) & 15, nt = (task >> 6) & 127, ks = (task >> 13) & 15;
    const int KS = type == 0 ? ks_w(rb) : (type == 1 ? 1 : ks_f(rb));
    const int tot = type == 0 ? 64 : (type == 1 ? 9 : 72);
    const int kp = kpart(tot, KS);
    const int nk = ks == KS - 1 ? tot - ks * kp : kp;
    float mean0 = 0.f, mean1 = 0.f, rstd0 = 0.f, rstd1 = 0.f;
    float acc[4 * NJ];
#pragma unroll
    for (int i = 0; i < 4 * NJ; i++) acc[i] = 0.f;
    for (int k = 0; k < nk; k++, it++) {
        const int st = it % G_ST;
        mbar_wait(tb + TB_FULL + 8 * st, (it / G_ST) & 1, dead);
        const uint64_t da = mk_desc(sb + st * G_STAGE + (tid >> 7) * 8192, 16, 1024), db = mk_desc(sb + st * G_STAGE + 16384, 8192, 1024);
        wg_fence();
#pragma unroll
        for (int kk = 0; kk < 4; kk++) wgmma_ss(acc, da + kk * 2, db + kk * 128, 1);
        wg_commit();
        if (type == 1 && k == 5) {
            const uint32_t sa = (NB == 1 ? sb + st * G_STAGE + 24576 : sb + T_AUX0) + lr * 8;
            ln_stats(sa, 9 / NB, (float)BN, mean0, rstd0);
            ln_stats(sa + 64, 9 / NB, (float)BN, mean1, rstd1);
            __syncwarp();
        }
        if (k > 0) {
            wg_wait<1>();
            if (lane == 0) mbar_arrive(tb + TB_EMPTY + 8 * ((it - 1) % G_ST));
        }
    }
    wg_wait<0>();
    if (lane == 0) mbar_arrive(tb + TB_EMPTY + 8 * ((it - 1) % G_ST));
    if (ks < KS - 1) {
        float4* part = g_part + (size_t)(((type >> 1) * 16 + rb) * 72 + nt * NJ) * 256 + tid;
        if (KS == 2) {
#pragma unroll
            for (int j = 0; j < NJ; j++) __stcg(part + j * 256, make_float4(acc[4 * j], acc[4 * j + 1], acc[4 * j + 2], acc[4 * j + 3]));
        } else {
#pragma unroll
            for (int j = 0; j < NJ; j++)
                asm volatile("red.relaxed.gpu.global.add.v4.f32 [%0],{%1,%2,%3,%4};" ::"l"(part + j * 256), "f"(acc[4 * j]), "f"(acc[4 * j + 1]),
                             "f"(acc[4 * j + 2]), "f"(acc[4 * j + 3]) : "memory");
        }
        store_acquire(tb, seq, dead);
        if (tid == 0) *store_task = task;
        mbar_arrive(tb + TB_SFULL);
        TLOG_END();
        return;
    }
    if (type != 1) {
        constexpr int NE = NB == 3 ? 4 : 2;
#pragma unroll
        for (int e = 0; e < NE; e++, it++) {
            const int st = it % G_ST;
            mbar_wait(tb + TB_FULL + 8 * st, (it / G_ST) & 1, dead);
            const uint32_t a = sb + st * G_STAGE;
            const int r0 = e * 16, r1 = NB == 3 ? (e == 0 ? 16 : (e == 1 ? 24 : 0)) : (e == 0 ? 8 : 0);
#pragma unroll
            for (int j = r0; j < r1; j += 2) {
                uint32_t rr[4];
                ldsm4(rr, a + ((j >> 3) & 1) * 16384 + mrow + ((((j & 7) + mchk) ^ mxor) << 4));
                float* q = &acc[4 * j];
                q[0] += bf_lo(rr[0]); q[1] += bf_hi(rr[0]); q[2] += bf_lo(rr[1]); q[3] += bf_hi(rr[1]);
                q[4] += bf_lo(rr[2]); q[5] += bf_hi(rr[2]); q[6] += bf_lo(rr[3]); q[7] += bf_hi(rr[3]);
            }
            if (e >= 1) {
                const int j0 = NB == 3 ? (e == 1 ? 20 : (e - 2) * 10) : 0, jn = NB == 3 ? (e == 1 ? 4 : 10) : 8;
#pragma unroll
                for (int j = 0; j < jn; j++) {
                    const float4 pv = lds128f(a + (NB == 3 && e == 1 ? 16384 : 0) + j * 4096 + tid * 16);
                    float* q = &acc[4 * (j0 + j)];
                    q[0] += pv.x; q[1] += pv.y; q[2] += pv.z; q[3] += pv.w;
                }
            }
            __syncwarp();
            if (lane == 0) mbar_arrive(tb + TB_EMPTY + 8 * st);
        }
    }
    uint32_t aux = sb + T_AUX0 + 3072;
    asm volatile("" : "+r"(aux)::"memory");
    uint32_t pk[2 * NJ];
    if (type == 2) {
#pragma unroll
        for (int j = 0; j < NJ; j++) {
            const float2 bv = ldsc64f(sb + T_B2 + (nt * BN + j * 8 + 2 * t) * 4);
            pk[2 * j] = pack_bf16(acc[4 * j] + bv.x, acc[4 * j + 1] + bv.y);
            pk[2 * j + 1] = pack_bf16(acc[4 * j + 2] + bv.x, acc[4 * j + 3] + bv.y);
        }
    } else if (type == 0) {
        float sm0 = 0.f, sm1 = 0.f;
#pragma unroll
        for (int j = 0; j < NJ; j++) {
            pk[2 * j] = pack_bf16(acc[4 * j], acc[4 * j + 1]);
            pk[2 * j + 1] = pack_bf16(acc[4 * j + 2], acc[4 * j + 3]);
            sm0 += bf_lo(pk[2 * j]) + bf_hi(pk[2 * j]);
            sm1 += bf_lo(pk[2 * j + 1]) + bf_hi(pk[2 * j + 1]);
        }
        sm0 += __shfl_xor_sync(~0u, sm0, 1); sm1 += __shfl_xor_sync(~0u, sm1, 1);
        sm0 += __shfl_xor_sync(~0u, sm0, 2); sm1 += __shfl_xor_sync(~0u, sm1, 2);
        sm0 *= (1.f / BN); sm1 *= (1.f / BN);
        float q0 = 0.f, q1 = 0.f;
#pragma unroll
        for (int j = 0; j < NJ; j++) {
            float d;
            d = bf_lo(pk[2 * j]) - sm0; q0 += d * d;
            d = bf_hi(pk[2 * j]) - sm0; q0 += d * d;
            d = bf_lo(pk[2 * j + 1]) - sm1; q1 += d * d;
            d = bf_hi(pk[2 * j + 1]) - sm1; q1 += d * d;
        }
        q0 += __shfl_xor_sync(~0u, q0, 1); q1 += __shfl_xor_sync(~0u, q1, 1);
        q0 += __shfl_xor_sync(~0u, q0, 2); q1 += __shfl_xor_sync(~0u, q1, 2);
        if (t == 0) {
            g_stat[(rb * 9 + nt) * 128 + lr] = make_float2(sm0, q0);
            g_stat[(rb * 9 + nt) * 128 + lr + 8] = make_float2(sm1, q1);
        }
    } else {
        rstd0 *= 0.5f; rstd1 *= 0.5f;
#pragma unroll
        for (int j = 0; j < NJ; j++) {
            const float4 c4 = ldsc128f(aux + (j * 8 + 2 * t) * 8);
            pk[2 * j] = pack_bf16(gelu_tanh(fmaf(rstd0, fmaf(-mean0, c4.x, acc[4 * j]), c4.y)), gelu_tanh(fmaf(rstd0, fmaf(-mean0, c4.z, acc[4 * j + 1]), c4.w)));
            pk[2 * j + 1] = pack_bf16(gelu_tanh(fmaf(rstd1, fmaf(-mean1, c4.x, acc[4 * j + 2]), c4.y)), gelu_tanh(fmaf(rstd1, fmaf(-mean1, c4.z, acc[4 * j + 3]), c4.w)));
        }
    }
    store_acquire(tb, seq, dead);
#pragma unroll
    for (int j = 0; j < NJ; j += 2)
        stsm4(sb + T_STG + mrow + (j >> 3) * 16384 + ((((j & 7) + mchk) ^ mxor) << 4), pk[2 * j], pk[2 * j + 1], pk[2 * j + 2], pk[2 * j + 3]);
    fence_async();
    if (tid == 0) *store_task = task;
    mbar_arrive(tb + TB_SFULL);
    TLOG_END();
}

__global__ void __launch_bounds__(384, 1)
k_tail(const __grid_constant__ CUtensorMap tmWo, const __grid_constant__ CUtensorMap tmW1, const __grid_constant__ CUtensorMap tmW2,
       const __grid_constant__ CUtensorMap tmX, const __grid_constant__ CUtensorMap tmOut,
       const __nv_bfloat16* __restrict__ w1, const __nv_bfloat16* __restrict__ b1, const __nv_bfloat16* __restrict__ b2) {
    extern __shared__ uint8_t smem_raw[];
    const uint32_t sb = (smem_u32(smem_raw) + 1023) & ~1023u;
    uint8_t* const smem = smem_raw + (sb - smem_u32(smem_raw));
    const uint32_t tb = sb + T_BAR;
    volatile int* tq = reinterpret_cast<volatile int*>(smem + T_BAR + TB_DATA);
    volatile int* store_task = tq + 8;
    const int lane = threadIdx.x & 31;
    const int warp = __shfl_sync(~0u, threadIdx.x >> 5, 0);
    int dead = 0;
    if (threadIdx.x == 0) {
        for (int i = 0; i < G_ST; i++) { mbar_init(tb + TB_FULL + 8 * i, 1); mbar_init(tb + TB_EMPTY + 8 * i, 8); }
        mbar_init(tb + TB_SQF, 1); mbar_init(tb + TB_SQE, 1); mbar_init(tb + TB_SFULL, 256); sts32(tb + TB_SEMPTY, 0u); *store_task = 0;
        for (int i = 0; i < 2; i++) { mbar_init(tb + TB_TQF + 8 * i, 1); mbar_init(tb + TB_TQE + 8 * i, 8); }
        asm volatile("fence.mbarrier_init.release.cluster;" ::: "memory");
    }
    for (int i = threadIdx.x; i < DM; i += 384) reinterpret_cast<float*>(smem + T_B2)[i] = __bfloat162float(b2[i]);
    __syncthreads();

    if (warp >= 8) {
      asm volatile("setmaxnreg.dec.sync.aligned.u32 40;");
      if (warp == 10) {
        uint32_t ns = 0;
        int idle = 0;
        if (T_START_DELAY && blockIdx.x < 36) {
            const uint32_t t0 = clk32();
            while ((int)(clk32() - t0) < T_START_DELAY) __nanosleep(500);
        }
        while (true) {
            if (idle == 0) {
                int n = 0;
                while (!mbar_try(tb + TB_SQE, (ns & 1) ^ 1)) { if (++n > (SPIN_LIMIT << 4)) { dead = 1; break; } }
                idle = 1;
            }
            int task = -1;
            const int ded = (int)blockIdx.x - DED0;
            if (DEDICATED && ded >= 0 && ded < 72 && ns < 3) {
                task = (int)ns | (15 << 2) | (ns == 1 ? ded << 6 : ((ded % 9) << 6) | ((ded / 9) << 13));
                if (lane == 0) { tq[4] = task; mbar_arrive(tb + TB_SQF); }
                ns++; idle = 0;
                continue;
            }
            uint4 f = make_uint4(0, 0, 0, 0), cn = make_uint4(999, 999, 999, 999);
            if (lane < 17) { f = ld_relaxed4(g_flag + lane * 32); if (lane < (DEDICATED ? 15 : 16)) cn = ld_relaxed4(g_flag + lane * 32 + 4); }
            const uint32_t init_done = __shfl_sync(~0u, f.x, 16), init_claimed = __shfl_sync(~0u, f.y, 16);
            const int lrb = lane & 15, lnt = ntile(lrb);
            const bool oW = cn.x < (uint32_t)(lnt * ks_w(lrb)), o1 = cn.y < (uint32_t)(8 * lnt), o2 = cn.z < (uint32_t)(lnt * ks_f(lrb));
            const uint32_t m2 = __ballot_sync(~0u, o2 && f.z >= (uint32_t)(8 * lnt)), m1 = __ballot_sync(~0u, o1 && f.y >= (uint32_t)lnt),
                           mW = __ballot_sync(~0u, oW && f.x >= 96u);
            const bool open = __any_sync(~0u, oW || o1 || o2);
            int q = -1, rbq = 0;
            if (init_claimed < (uint32_t)NINIT) q = 3;
            else if (init_done >= (uint32_t)NINIT) {
                if (mW) { q = 0; rbq = __ffs(mW) - 1; }
                else if (m1) { q = 1; rbq = __ffs(m1) - 1; }
                else if (m2) { q = 2; rbq = __ffs(m2) - 1; }
            }
            if (q >= 0) {
                if (lane == 0) {
                    const int nq = ntile(rbq);
                    const int n = q == 3 ? NINIT : (q == 1 ? 8 * nq : nq * (q == 2 ? ks_f(rbq) : ks_w(rbq)));
                    uint32_t idx;
                    asm volatile("atom.acquire.gpu.global.add.u32 %0,[%1],1;" : "=r"(idx) : "l"(g_flag + (q == 3 ? FL_CINIT : rbq * 32 + FL_CW + q)) : "memory");
                    if ((int)idx < n) {
                        if (q == 3) task = 3 | (idx << 2);
                        else if (q == 1) task = 1 | (rbq << 2) | (idx << 6);
                        else task = q | (rbq << 2) | ((idx % nq) << 6) | ((idx / nq) << 13);
                    }
                }
                task = __shfl_sync(~0u, task, 0);
                if (task < 0) continue;
            } else {
                if (!open || dead || ++idle > (1 << 16)) task = -2;
                else { __nanosleep(100); continue; }
            }
            if (lane == 0) { tq[4] = task; mbar_arrive(tb + TB_SQF); }
            ns++; idle = 0;
            if (task < 0) break;
        }
      } else if (warp == 8) {
        uint32_t it = 0, seq = 0;
        for (uint32_t ns = 0;; ns++) {
            int task = -2;
            if (lane == 0) {
                int n0 = 0;
                while (!mbar_try(tb + TB_SQF, ns & 1)) { if (++n0 > (SPIN_LIMIT << 4)) { dead = 1; break; } }
                if (!dead) task = tq[4];
                const int type = task & 3, rb = (task >> 2) & 15, nt = (task >> 6) & 127, ks = (task >> 13) & 15;
                for (int rep = 0; rep < 1; rep++, seq++) {
                    const int wq = seq & 1;
                    int n = 0;
                    while (!mbar_try(tb + TB_TQE + 8 * wq, ((seq >> 1) & 1) ^ 1)) { if (++n > (SPIN_LIMIT << 4)) { dead = 1; break; } }
                    tq[2 * wq] = task; tq[2 * wq + 1] = (int)it;
                    mbar_arrive(tb + TB_TQF + 8 * wq);
                }
                if (task >= 0 && type == 3) mbar_arrive(tb + TB_SQE);
                if (task >= 0 && type != 3) {
                    asm volatile("fence.proxy.async;" ::: "memory");
                    const int nb = small_rb(rb) ? 1 : 3;
                    int KS, tot;
                    const uint8_t* A;
                    const CUtensorMap* tm;
                    if (type == 0) { KS = ks_w(rb); tot = 64; A = g_ox + (size_t)rb * 64 * 16384; tm = &tmWo; }
                    else if (type == 1) { KS = 1; tot = 9; A = g_hb + (size_t)rb * 9 * 16384; tm = &tmW1; }
                    else { KS = ks_f(rb); tot = 72; A = g_ff + (size_t)rb * 72 * 16384; tm = &tmW2; }
                    const int kp = kpart(tot, KS), k1 = ks == KS - 1 ? tot : ks * kp + kp;
                    int k0 = ks * kp;
                    if (DEDICATED && rb == 15) {
                        for (int i = 0; i < G_ST; i++) {
                            const int st = (it + i) % G_ST;
                            mbar_wait(tb + TB_EMPTY + 8 * st, (((it + i) / G_ST) & 1) ^ 1, dead);
                            mbar_expect_tx(tb + TB_FULL + 8 * st, 16384 + 8192);
                            tma2d(sb + st * G_STAGE + 16384, tm, nt * 64, (k0 + i) * 64, tb + TB_FULL + 8 * st);
                        }
                        const uint32_t need = type == 0 ? 96u : (type == 1 ? 9u : 72u);
                        int n = 0;
                        while (ld_acquire1(g_flag + 15 * 32 + type) < need || (type == 0 && ld_relaxed1(g_flag + FL_INIT) < (uint32_t)NINIT)) {
                            if (++n > (SPIN_LIMIT << 2)) { dead = 1; break; }
                        }
                        asm volatile("fence.proxy.async;" ::: "memory");
                        for (int i = 0; i < G_ST; i++, it++, k0++) bulk_g2s(sb + (it % G_ST) * G_STAGE, A + (size_t)k0 * 16384, 16384, tb + TB_FULL + 8 * (it % G_ST));
                    }
                    for (int k = k0; k < k1; k++, it++) {
                        const int st = it % G_ST;
                        mbar_wait(tb + TB_EMPTY + 8 * st, ((it / G_ST) & 1) ^ 1, dead);
                        if (k == k1 - SCHED_AHEAD && !(type != 1 && ks == KS - 1)) mbar_arrive(tb + TB_SQE);
                        const uint32_t a = sb + st * G_STAGE, bb = a + 16384, fb = tb + TB_FULL + 8 * st;
                        const bool aux = type == 1 && k == 5;
                        mbar_expect_tx(fb, 16384 + nb * 8192 + (aux ? (9 / nb) * 1024 + nb * 512 : 0));
                        bulk_g2s(a, A + (size_t)k * 16384, 16384, fb);
                        for (int i = 0; i < nb; i++) tma2d(bb + i * 8192, tm, (nt * nb + i) * 64, k * 64, fb);
                        if (aux) {
                            const uint32_t ax = sb + T_AUX0;
                            bulk_g2s(nb == 3 ? ax : a + 24576, g_stat + rb * 9 * 128, (9 / nb) * 1024, fb);
                            bulk_g2s(ax + 3072, g_cb + nt * nb * 64, nb * 512, fb);
                        }
                    }
                    if (type != 1 && ks == KS - 1) {
                        const uint8_t* part = reinterpret_cast<const uint8_t*>(g_part + (size_t)(((type >> 1) * 16 + rb) * 72 + nt * nb * 8) * 256);
                        const int ne = nb == 3 ? 4 : 2;
                        for (int e = 0; e < ne; e++, it++) {
                            const int st = it % G_ST;
                            mbar_wait(tb + TB_EMPTY + 8 * st, ((it / G_ST) & 1) ^ 1, dead);
                            const uint32_t a = sb + st * G_STAGE, fb = tb + TB_FULL + 8 * st;
                            mbar_expect_tx(fb, nb == 3 ? (e < 2 ? 32768 : 40960) : (e == 0 ? 16384 : 32768));
                            for (int i = 2 * e; i < nb && i < 2 * e + 2; i++) {
                                if (type == 0) tma2d(a + (i & 1) * 16384, &tmX, (nt * nb + i) * 64, rb * 128, fb);
                                else bulk_g2s(a + (i & 1) * 16384, g_hb + (size_t)(rb * 9 + nt * nb + i) * 16384, 16384, fb);
                            }
                            if (e == 1) {
                                const uint32_t* dn = g_flag + rb * 32 + FL_DONE + (type >> 1) * 9 + nt;
                                int n = 0;
                                while (ld_acquire1(dn) < (uint32_t)(KS - 1)) { if (++n > SPIN_LIMIT) { dead = 1; break; } __nanosleep(20); }
                                asm volatile("fence.proxy.async;" ::: "memory");
                                if (nb == 3) bulk_g2s(a + 16384, part + 81920, 16384, fb);
                                else bulk_g2s(a, part, 32768, fb);
                            } else if (e >= 2) bulk_g2s(a, part + (e - 2) * 40960, 40960, fb);
                        }
                        mbar_arrive(tb + TB_SQE);
                    }
                }
            }
            task = __shfl_sync(~0u, task, 0);
            if (task < 0) break;
        }
      } else if (warp == 9) {
        if (lane == 0) {
            uint32_t ph = 0, rel = 0;
            while (true) {
                int n = 0;
                while (!mbar_try(tb + TB_SFULL, ph)) { if (++n > (SPIN_LIMIT << 4)) { dead = 1; break; } }
                if (dead) break;
                const int task = *store_task;
                if (task < 0) break;
                const int type = task & 3, rb = (task >> 2) & 15, nt = (task >> 6) & 127, ks = (task >> 13) & 15;
                const int nb = small_rb(rb) ? 1 : 3;
                uint32_t* flag = nullptr;
                bool stored = true;
                if (type == 3) { flag = g_flag + FL_INIT; stored = false; }
                else if (type == 1) { flag = g_flag + rb * 32 + FL_FF; bulk_s2g(g_ff + (size_t)(rb * 72 + nt * nb) * 16384, sb + T_STG, nb * 16384); }
                else if (ks < (type == 0 ? ks_w(rb) : ks_f(rb)) - 1) { flag = g_flag + rb * 32 + FL_DONE + (type >> 1) * 9 + nt; stored = false; }
                else if (type == 0) { flag = g_flag + rb * 32 + FL_H; bulk_s2g(g_hb + (size_t)(rb * 9 + nt * nb) * 16384, sb + T_STG, nb * 16384); }
                else for (int i = 0; i < nb; i++) tma2d_store(&tmOut, sb + T_STG + i * 16384, (nt * nb + i) * 64, rb * 128);
                if (stored) {
                    asm volatile("cp.async.bulk.commit_group;\ncp.async.bulk.wait_group.read 0;" ::: "memory");
                    asm volatile("st.volatile.shared.u32 [%0],%1;" ::"r"(tb + TB_SEMPTY), "r"(++rel) : "memory");
                    asm volatile("cp.async.bulk.wait_group 0;\nfence.proxy.async;" ::: "memory");
                } else asm volatile("st.volatile.shared.u32 [%0],%1;" ::"r"(tb + TB_SEMPTY), "r"(++rel) : "memory");
                if (flag) asm volatile("red.release.gpu.global.add.u32 [%0],1;" ::"l"(flag) : "memory");
                ph ^= 1;
            }
            pdl_wait();
            asm volatile("fence.acq_rel.gpu;" ::: "memory");
            if (atomicAdd(g_flag + FL_EXIT, 1u) == gridDim.x - 1) {
                for (int i = 0; i < 17 * 8; i++) reinterpret_cast<uint4*>(g_flag)[i] = make_uint4(0, 0, 0, 0);
            }
        }
      }
    } else {
        asm volatile("setmaxnreg.inc.sync.aligned.u32 232;");
        const int tid = threadIdx.x;
        for (uint32_t seq = 0;; seq++) {
            const int wq = seq & 1;
            {
                int m = 0;
                while (!mbar_try(tb + TB_TQF + 8 * wq, (seq >> 1) & 1)) { if (++m > (SPIN_LIMIT << 4)) { dead = 1; break; } }
            }
            const int task = dead ? -1 : tq[2 * wq];
            const uint32_t it = (uint32_t)tq[2 * wq + 1];
            __syncwarp();
            if (lane == 0) mbar_arrive(tb + TB_TQE + 8 * wq);
            if (task < 0) {
                store_acquire(tb, seq, dead);
                if (tid == 0) *store_task = -1;
                mbar_arrive(tb + TB_SFULL);
                break;
            }
            if ((task & 3) == 3) {
                const int idx = task >> 2;
                store_acquire(tb, seq, dead);
                float a8[8] = {0.f, 0.f, 0.f, 0.f, 0.f, 0.f, 0.f, 0.f};
                const uint4* src = reinterpret_cast<const uint4*>(w1 + idx * 128 + (tid & 15) * 8);
#pragma unroll 12
                for (int k = tid >> 4; k < DM; k += 16) {
                    const uint4 v = src[(size_t)k * (FF / 8)];
                    const uint32_t wv[4] = {v.x, v.y, v.z, v.w};
#pragma unroll
                    for (int j = 0; j < 4; j++) { a8[2 * j] += bf_lo(wv[j]); a8[2 * j + 1] += bf_hi(wv[j]); }
                }
                float* red = reinterpret_cast<float*>(smem + T_STG);
#pragma unroll
                for (int j = 0; j < 8; j++) red[(tid >> 4) * 128 + (tid & 15) * 8 + j] = a8[j];
                bar_sync(1, 256);
                if (tid < 128) {
                    float sum = 0.f;
#pragma unroll
                    for (int j = 0; j < 16; j++) sum += red[j * 128 + tid];
                    g_cb[idx * 128 + tid] = make_float2(sum, 0.5f * __bfloat162float(b1[idx * 128 + tid]));
                }
                for (int u = idx; u < 96; u += NINIT) {
                    const int rbu = (u / 3) & 15;
                    if ((u < 48 ? ks_w(rbu) : ks_f(rbu)) > 2)
                        for (int j = 0; j < 24; j++) g_part[((size_t)u * 24 + j) * 256 + tid] = make_float4(0.f, 0.f, 0.f, 0.f);
                }
                if (tid == 0) *store_task = task;
                mbar_arrive(tb + TB_SFULL);
                TLOG_END();
            } else if (small_rb((task >> 2) & 15)) tail_task<1>(sb, store_task, task, it, seq, tid, dead);
            else tail_task<3>(sb, store_task, task, it, seq, tid, dead);
        }
    }
}

typedef CUresult (*EncodeFn)(CUtensorMap*, CUtensorMapDataType, cuuint32_t, void*, const cuuint64_t*, const cuuint64_t*,
                             const cuuint32_t*, const cuuint32_t*, CUtensorMapInterleave, CUtensorMapSwizzle,
                             CUtensorMapL2promotion, CUtensorMapFloatOOBfill);

void make_map(EncodeFn enc, CUtensorMap* tm, const void* ptr, uint64_t inner, uint64_t outer, uint32_t box_inner, uint32_t box_outer) {
    cuuint64_t dims[2] = {inner, outer};
    cuuint64_t strides[1] = {inner * 2};
    cuuint32_t box[2] = {box_inner, box_outer};
    cuuint32_t es[2] = {1, 1};
    enc(tm, CU_TENSOR_MAP_DATA_TYPE_BFLOAT16, 2, const_cast<void*>(ptr), dims, strides, box, es, CU_TENSOR_MAP_INTERLEAVE_NONE,
        CU_TENSOR_MAP_SWIZZLE_128B, CU_TENSOR_MAP_L2_PROMOTION_L2_256B, CU_TENSOR_MAP_FLOAT_OOB_FILL_NONE);
}

}

extern "C" void kernel_launch(void* const* d_in, const int* in_sizes, int n_in, void* d_out, int out_size) {
    const __nv_bfloat16* x = (const __nv_bfloat16*)d_in[0];
    const __nv_bfloat16* mem0 = (const __nv_bfloat16*)d_in[1];
    const __nv_bfloat16* Wq = (const __nv_bfloat16*)d_in[2];
    const __nv_bfloat16* Wk = (const __nv_bfloat16*)d_in[3];
    const __nv_bfloat16* Wv = (const __nv_bfloat16*)d_in[4];
    const __nv_bfloat16* Wo = (const __nv_bfloat16*)d_in[5];
    const __nv_bfloat16* w1 = (const __nv_bfloat16*)d_in[8];
    const __nv_bfloat16* b1 = (const __nv_bfloat16*)d_in[9];
    const __nv_bfloat16* w2 = (const __nv_bfloat16*)d_in[10];
    const __nv_bfloat16* b2 = (const __nv_bfloat16*)d_in[11];
    __nv_bfloat16* out = (__nv_bfloat16*)d_out;
    cudaStream_t stream = cudaStreamPerThread;

    static EncodeFn enc = nullptr;
    if (!enc) {
        cudaDriverEntryPointQueryResult qr;
        void* fn = nullptr;
        cudaGetDriverEntryPoint("cuTensorMapEncodeTiled", &fn, cudaEnableDefault, &qr);
        enc = (EncodeFn)fn;
        cudaFuncSetAttribute(k_chain, cudaFuncAttributeMaxDynamicSharedMemorySize, SM_CHAIN_BYTES);
        cudaFuncSetAttribute(k_tail, cudaFuncAttributeMaxDynamicSharedMemorySize, T_SMEM);
    }
    CUtensorMap tWq, tWk, tWv, tWo, tW1, tW2, tX, tOut;
    make_map(enc, &tWq, Wq, HD, DM, 64, 192);
    make_map(enc, &tWk, Wk, HD, DM, 64, 192);
    make_map(enc, &tWv, Wv, HD, DM, 64, 192);
    make_map(enc, &tX, x, DM, SEQ, 64, 128);
    make_map(enc, &tOut, out, DM, SEQ, 64, 128);
    make_map(enc, &tWo, Wo, DM, HD, 64, 64);
    make_map(enc, &tW1, w1, FF, DM, 64, 64);
    make_map(enc, &tW2, w2, DM, FF, 64, 64);

    {
        cudaLaunchConfig_t cfg = {};
        cfg.gridDim = dim3(96); cfg.blockDim = dim3(384); cfg.dynamicSmemBytes = SM_CHAIN_BYTES; cfg.stream = stream;
        void* px;
        cudaGetSymbolAddress(&px, g_xch);
        uint8_t* xb = reinterpret_cast<uint8_t*>((reinterpret_cast<uintptr_t>(px) + 65535) & ~(uintptr_t)65535);
        cudaLaunchKernelEx(&cfg, k_chain, tWq, tWk, tWv, tWo, x, mem0, xb);
    }
    {
        cudaLaunchConfig_t cfg = {};
        cfg.gridDim = dim3(132); cfg.blockDim = dim3(384); cfg.dynamicSmemBytes = T_SMEM; cfg.stream = stream;
        cudaLaunchAttribute at[1];
        at[0].id = cudaLaunchAttributeProgrammaticStreamSerialization;
        at[0].val.programmaticStreamSerializationAllowed = 1;
        cfg.attrs = at; cfg.numAttrs = 1;
        cudaLaunchKernelEx(&cfg, k_tail, tWo, tW1, tW2, tX, tOut, w1, b1, b2);
    }
}
```

```cpp
#include <cuda_runtime.h>
#include <cuda_bf16.h>
#include <cuda.h>
#include <stdint.h>

namespace {

constexpr int SEQ = 2048, DM = 576, DH = 128, NSEG = 64, FF = 4608, HD = 4096;
constexpr int XN_SEG_BYTES = 32 * DM * 2;
constexpr int SPIN_LIMIT = 1 << 20;

__device__ __align__(1024) uint8_t g_xn[NSEG * XN_SEG_BYTES];
__device__ __align__(1024) uint8_t g_ox[SEQ * HD * 2];
__device__ __align__(1024) uint8_t g_xch[(96 + 3) * 65536];
__device__ uint32_t g_tab[128];
__device__ __align__(1024) uint8_t g_hb[SEQ * DM * 2];
__device__ __align__(1024) uint8_t g_ff[SEQ * FF * 2];
__device__ __align__(1024) float4 g_part[2 * 16 * 3 * 24 * 256];
__device__ __align__(128) float2 g_stat[16 * 9 * 128];
__device__ __align__(128) float2 g_cb[FF];
constexpr int FL_OX = 0, FL_H = 1, FL_FF = 2, FL_CW = 4, FL_C1 = 5, FL_C2 = 6, FL_DONE = 8  , FL_INIT = 512, FL_CINIT = 513, FL_EXIT = 514;
__device__ __align__(128) uint32_t g_flag[17 * 32];
#define TLOG_END()
#define PSTAMP(i)

__device__ __forceinline__ uint32_t smem_u32(const void* p) { return (uint32_t)__cvta_generic_to_shared(p); }
__device__ __forceinline__ uint32_t mapa(uint32_t a, uint32_t r) {
    uint32_t o; asm("mapa.shared::cluster.u32 %0,%1,%2;" : "=r"(o) : "r"(a), "r"(r)); return o;
}
__device__ __forceinline__ void mbar_init(uint32_t bar, uint32_t cnt) {
    asm volatile("mbarrier.init.shared::cta.b64 [%0],%1;" ::"r"(bar), "r"(cnt) : "memory");
}
__device__ __forceinline__ void mbar_expect_tx(uint32_t bar, uint32_t bytes) {
    asm volatile("mbarrier.arrive.expect_tx.shared::cta.b64 _,[%0],%1;" ::"r"(bar), "r"(bytes) : "memory");
}
__device__ __forceinline__ void mbar_arrive(uint32_t bar) {
    asm volatile("mbarrier.arrive.shared::cta.b64 _,[%0];" ::"r"(bar) : "memory");
}
__device__ __forceinline__ bool mbar_try(uint32_t bar, uint32_t ph) {
    uint32_t ok;
    asm volatile("{.reg .pred p; mbarrier.try_wait.parity.shared::cta.b64 p,[%1],%2; selp.u32 %0,1,0,p;}"
                 : "=r"(ok) : "r"(bar), "r"(ph) : "memory");
    return ok;
}
__device__ __forceinline__ void mbar_wait(uint32_t bar, uint32_t ph, int& dead) {
    if (mbar_try(bar, ph)) return;
    int n = dead ? SPIN_LIMIT : 0;
#pragma unroll 1
    while (!mbar_try(bar, ph)) { if (++n > SPIN_LIMIT) { dead = 1; break; } }
}
__device__ __forceinline__ void bar_sync(int id, int n) { asm volatile("bar.sync %0,%1;" ::"r"(id), "r"(n) : "memory"); }
__device__ __forceinline__ void bar_arrive(int id, int n) { asm volatile("bar.arrive %0,%1;" ::"r"(id), "r"(n) : "memory"); }
__device__ __forceinline__ void cluster_sync() {
    asm volatile("barrier.cluster.arrive.release.aligned;\nbarrier.cluster.wait.acquire.aligned;" ::: "memory");
}
__device__ __forceinline__ void fence_async_g() { asm volatile("fence.proxy.async.global;" ::: "memory"); }
__device__ __forceinline__ void fence_async() { asm volatile("fence.proxy.async.shared::cta;" ::: "memory"); }

__device__ __forceinline__ void ldsm4(uint32_t (&r)[4], uint32_t a) {
    asm volatile("ldmatrix.sync.aligned.m8n8.x4.shared.b16 {%0,%1,%2,%3},[%4];"
                 : "=r"(r[0]), "=r"(r[1]), "=r"(r[2]), "=r"(r[3]) : "r"(a) : "memory");
}
__device__ __forceinline__ void ldsm4t(uint32_t (&r)[4], uint32_t a) {
    asm volatile("ldmatrix.sync.aligned.m8n8.x4.trans.shared.b16 {%0,%1,%2,%3},[%4];"
                 : "=r"(r[0]), "=r"(r[1]), "=r"(r[2]), "=r"(r[3]) : "r"(a) : "memory");
}
__device__ __forceinline__ void stsm4(uint32_t a, uint32_t r0, uint32_t r1, uint32_t r2, uint32_t r3) {
    asm volatile("stmatrix.sync.aligned.m8n8.x4.shared.b16 [%0],{%1,%2,%3,%4};" ::"r"(a), "r"(r0), "r"(r1), "r"(r2), "r"(r3) : "memory");
}
__device__ __forceinline__ void stsm4t(uint32_t a, uint32_t r0, uint32_t r1, uint32_t r2, uint32_t r3) {
    asm volatile("stmatrix.sync.aligned.m8n8.x4.trans.shared.b16 [%0],{%1,%2,%3,%4};" ::"r"(a), "r"(r0), "r"(r1), "r"(r2), "r"(r3) : "memory");
}
__device__ __forceinline__ void mma16(float (&d)[4], uint32_t a0, uint32_t a1, uint32_t a2, uint32_t a3, uint32_t b0, uint32_t b1) {
    asm volatile("mma.sync.aligned.m16n8k16.row.col.f32.bf16.bf16.f32 {%0,%1,%2,%3},{%4,%5,%6,%7},{%8,%9},{%0,%1,%2,%3};"
                 : "+f"(d[0]), "+f"(d[1]), "+f"(d[2]), "+f"(d[3]) : "r"(a0), "r"(a1), "r"(a2), "r"(a3), "r"(b0), "r"(b1));
}
__device__ __forceinline__ void mma8(float (&d)[4], uint32_t a0, uint32_t a1, uint32_t b0) {
    asm volatile("mma.sync.aligned.m16n8k8.row.col.f32.bf16.bf16.f32 {%0,%1,%2,%3},{%4,%5},{%6},{%0,%1,%2,%3};"
                 : "+f"(d[0]), "+f"(d[1]), "+f"(d[2]), "+f"(d[3]) : "r"(a0), "r"(a1), "r"(b0));
}
__device__ __forceinline__ uint32_t pack_bf16(float lo, float hi) {
    uint32_t r; asm("cvt.rn.bf16x2.f32 %0,%1,%2;" : "=r"(r) : "f"(hi), "f"(lo)); return r;
}
__device__ __forceinline__ float bf_lo(uint32_t w) { return __uint_as_float(w << 16); }
__device__ __forceinline__ float bf_hi(uint32_t w) { return __uint_as_float(w & 0xffff0000u); }
__device__ __forceinline__ float ex2(float x) { float r; asm("ex2.approx.ftz.f32 %0,%1;" : "=f"(r) : "f"(x)); return r; }
__device__ __forceinline__ void st_async32(uint32_t dst, uint32_t v, uint32_t bar) {
    asm volatile("st.async.shared::cluster.mbarrier::complete_tx::bytes.u32 [%0],%1,[%2];" ::"r"(dst), "r"(v), "r"(bar) : "memory");
}
__device__ __forceinline__ void bulk_g2s(uint32_t dst, const void* src, uint32_t bytes, uint32_t bar) {
    asm volatile("cp.async.bulk.shared::cluster.global.mbarrier::complete_tx::bytes [%0],[%1],%2,[%3];"
                 ::"r"(dst), "l"(src), "r"(bytes), "r"(bar) : "memory");
}
__device__ __forceinline__ void bulk_g2s_mc(uint32_t dst, const void* src, uint32_t bytes, uint32_t bar, uint16_t mask) {
    asm volatile("cp.async.bulk.shared::cluster.global.mbarrier::complete_tx::bytes.multicast::cluster [%0],[%1],%2,[%3],%4;"
                 ::"r"(dst), "l"(src), "r"(bytes), "r"(bar), "h"(mask) : "memory");
}
__device__ __forceinline__ void bulk_s2s(uint32_t dst, uint32_t src, uint32_t bytes, uint32_t bar) {
    asm volatile("cp.async.bulk.shared::cluster.shared::cta.mbarrier::complete_tx::bytes [%0],[%1],%2,[%3];"
                 ::"r"(dst), "r"(src), "r"(bytes), "r"(bar) : "memory");
}
__device__ __forceinline__ void tma2d(uint32_t dst, const CUtensorMap* tm, int c0, int c1, uint32_t bar) {
    asm volatile("cp.async.bulk.tensor.2d.shared::cluster.global.mbarrier::complete_tx::bytes [%0],[%1,{%3,%4}],[%2];"
                 ::"r"(dst), "l"(tm), "r"(bar), "r"(c0), "r"(c1) : "memory");
}
__device__ __forceinline__ uint4 ld_relaxed4(const void* p) {
    uint4 v;
    asm volatile("ld.relaxed.gpu.global.v4.u32 {%0,%1,%2,%3},[%4];" : "=r"(v.x), "=r"(v.y), "=r"(v.z), "=r"(v.w) : "l"(p) : "memory");
    return v;
}
__device__ __forceinline__ void st_relaxed1(void* p, uint32_t a) {
    asm volatile("st.relaxed.gpu.global.u32 [%0],%1;" ::"l"(p), "r"(a) : "memory");
}
__device__ __forceinline__ uint32_t ld_relaxed1(const void* p) {
    uint32_t v; asm volatile("ld.relaxed.gpu.global.u32 %0,[%1];" : "=r"(v) : "l"(p) : "memory"); return v;
}
__device__ __forceinline__ void red_add1(uint32_t* p) { asm volatile("red.relaxed.gpu.global.add.u32 [%0],1;" ::"l"(p) : "memory"); }
__device__ __forceinline__ void sts128(uint32_t a, uint4 v) {
    asm volatile("st.shared.v4.u32 [%0],{%1,%2,%3,%4};" ::"r"(a), "r"(v.x), "r"(v.y), "r"(v.z), "r"(v.w) : "memory");
}
__device__ __forceinline__ uint4 lds128(uint32_t a) {
    uint4 v; asm volatile("ld.shared.v4.u32 {%0,%1,%2,%3},[%4];" : "=r"(v.x), "=r"(v.y), "=r"(v.z), "=r"(v.w) : "r"(a) : "memory");
    return v;
}
__device__ __forceinline__ void sts32f(uint32_t a, float v) { asm volatile("st.shared.f32 [%0],%1;" ::"r"(a), "f"(v) : "memory"); }
__device__ __forceinline__ float2 lds64f(uint32_t a) {
    float2 v; asm volatile("ld.shared.v2.f32 {%0,%1},[%2];" : "=f"(v.x), "=f"(v.y) : "r"(a) : "memory"); return v;
}
__device__ __forceinline__ void wg_fence() { asm volatile("wgmma.fence.sync.aligned;" ::: "memory"); }
__device__ __forceinline__ void wg_commit() { asm volatile("wgmma.commit_group.sync.aligned;" ::: "memory"); }
template <int N> __device__ __forceinline__ void wg_wait() { asm volatile("wgmma.wait_group.sync.aligned %0;" ::"n"(N) : "memory"); }
__device__ __forceinline__ uint64_t mk_desc(uint32_t addr, uint32_t lbo, uint32_t sbo) {
    return (uint64_t)((addr & 0x3FFFF) >> 4) | ((uint64_t)(lbo >> 4) << 16) | ((uint64_t)(sbo >> 4) << 32) | (1ull << 62);
}
__device__ __forceinline__ void wgmma_n32_rs(float (&d)[16], const uint32_t (&a)[4], uint64_t desc, int scale_d) {
    asm volatile("{.reg .pred p; setp.ne.b32 p,%21,0;\n"
                 "wgmma.mma_async.sync.aligned.m64n32k16.f32.bf16.bf16 "
                 "{%0,%1,%2,%3,%4,%5,%6,%7,%8,%9,%10,%11,%12,%13,%14,%15},{%16,%17,%18,%19},%20,p,1,1,0;}"
                 : "+f"(d[0]), "+f"(d[1]), "+f"(d[2]), "+f"(d[3]), "+f"(d[4]), "+f"(d[5]), "+f"(d[6]), "+f"(d[7]),
                   "+f"(d[8]), "+f"(d[9]), "+f"(d[10]), "+f"(d[11]), "+f"(d[12]), "+f"(d[13]), "+f"(d[14]), "+f"(d[15])
                 : "r"(a[0]), "r"(a[1]), "r"(a[2]), "r"(a[3]), "l"(desc), "r"(scale_d));
}
__device__ __forceinline__ void wgmma_n32_ss(float (&d)[16], uint64_t da, uint64_t desc) {
    asm volatile("wgmma.mma_async.sync.aligned.m64n32k16.f32.bf16.bf16 "
                 "{%0,%1,%2,%3,%4,%5,%6,%7,%8,%9,%10,%11,%12,%13,%14,%15},%16,%17,1,1,1,0,0;"
                 : "+f"(d[0]), "+f"(d[1]), "+f"(d[2]), "+f"(d[3]), "+f"(d[4]), "+f"(d[5]), "+f"(d[6]), "+f"(d[7]),
                   "+f"(d[8]), "+f"(d[9]), "+f"(d[10]), "+f"(d[11]), "+f"(d[12]), "+f"(d[13]), "+f"(d[14]), "+f"(d[15])
                 : "l"(da), "l"(desc));
}
__device__ __forceinline__ void pdl_wait() { asm volatile("griddepcontrol.wait;" ::: "memory"); }
__device__ __forceinline__ void pdl_launch() { asm volatile("griddepcontrol.launch_dependents;" ::: "memory"); }

__device__ __forceinline__ void ln_load(uint4 (&v)[3], const __nv_bfloat16* __restrict__ x, int row, int lane) {
    const uint4* src = reinterpret_cast<const uint4*>(x + (size_t)row * DM);
#pragma unroll
    for (int i = 0; i < 3; i++) {
        v[i] = make_uint4(0, 0, 0, 0);
        if (lane + 32 * i < 72 && row < SEQ)
            asm volatile("ld.global.nc.v4.u32 {%0,%1,%2,%3},[%4];" : "=r"(v[i].x), "=r"(v[i].y), "=r"(v[i].z), "=r"(v[i].w) : "l"(src + lane + 32 * i));
    }
}
__device__ __forceinline__ void ln_row(const uint4 (&v)[3], int row, int lane) {
    float f[24];
    float sum = 0.f;
#pragma unroll
    for (int i = 0; i < 3; i++) {
        const uint32_t w[4] = {v[i].x, v[i].y, v[i].z, v[i].w};
#pragma unroll
        for (int j = 0; j < 4; j++) {
            f[i * 8 + 2 * j] = __uint_as_float(w[j] << 16);
            f[i * 8 + 2 * j + 1] = __uint_as_float(w[j] & 0xffff0000u);
            sum += f[i * 8 + 2 * j] + f[i * 8 + 2 * j + 1];
        }
    }
#pragma unroll
    for (int o = 16; o; o >>= 1) sum += __shfl_xor_sync(~0u, sum, o);
    const float mean = sum * (1.f / DM);
    float var = 0.f;
#pragma unroll
    for (int i = 0; i < 3; i++) {
        if (lane + 32 * i < 72) {
#pragma unroll
            for (int j = 0; j < 8; j++) { float d = f[i * 8 + j] - mean; var += d * d; }
        }
    }
#pragma unroll
    for (int o = 16; o; o >>= 1) var += __shfl_xor_sync(~0u, var, o);
    const float rstd = rsqrtf(var * (1.f / DM) + 1e-5f);
    const int seg = row >> 5, r = row & 31;
#pragma unroll
    for (int i = 0; i < 3; i++) {
        const int c = lane + 32 * i;
        if (c < 72) {
            uint4 o;
            o.x = pack_bf16((f[i * 8 + 0] - mean) * rstd, (f[i * 8 + 1] - mean) * rstd);
            o.y = pack_bf16((f[i * 8 + 2] - mean) * rstd, (f[i * 8 + 3] - mean) * rstd);
            o.z = pack_bf16((f[i * 8 + 4] - mean) * rstd, (f[i * 8 + 5] - mean) * rstd);
            o.w = pack_bf16((f[i * 8 + 6] - mean) * rstd, (f[i * 8 + 7] - mean) * rstd);
            *reinterpret_cast<uint4*>(g_xn + (size_t)seg * XN_SEG_BYTES + (c >> 3) * 4096 + r * 128 + (((c & 7) ^ (r & 7)) << 4)) = o;
        }
    }
}

constexpr int SM_XN = 0;
constexpr int SM_X = 73728;
constexpr int SM_MB = SM_X + 3 * 24576;
constexpr int SXR = 56;
constexpr int SMR = 80;
constexpr int SM_SX = SM_MB + 3 * 6144;
constexpr int SM_SXX = SM_SX + 8 * SMR * 4;
constexpr int SM_OT = SM_SXX + 16 * SXR * 4;
constexpr int SM_OX = SM_OT + 2048;
constexpr int SM_MAIN_END = SM_OX + 4096;
constexpr int SM_STG_W = XN_SEG_BYTES;
constexpr int SM_MEMT = SM_STG_W + 147456;
#define NREGK 33
constexpr int NREG_K = NREGK;
constexpr int SM_WS = SM_MEMT + 9216;
constexpr int SM_TAB = SM_WS + (36 - NREG_K) * 4096;
constexpr int SM_AUX = SM_TAB + 4096;
constexpr int SM_BAR = SM_AUX + 12288;
constexpr int SM_TIM = SM_BAR + 128;
constexpr int SM_CHAIN_BYTES = SM_TIM + 1024;
static_assert(SM_MAIN_END <= SM_MEMT && SM_TAB % 1024 == 0 && SM_STG_W % 1024 == 0, "smem");
static_assert(SM_CHAIN_BYTES <= 232448, "smem");
constexpr int BAR_MEM = 1, BAR_GO = 2, BAR_A = 3, BAR_B = 4, BAR_QD = 5, BAR_GO2 = 6, BAR_S = 7, BAR_U = 8, BAR_OX = 9;
#define BULK1 22

__device__ __forceinline__ uint32_t clk32() { uint32_t t; asm volatile("mov.u32 %0,%%clock;" : "=r"(t)::"memory"); return t; }
#define TSTAMP(i)
#define TFLUSH()

__device__ __forceinline__ uint32_t ld_acquire1(const void* p) {
    uint32_t v; asm volatile("ld.acquire.gpu.global.u32 %0,[%1];" : "=r"(v) : "l"(p) : "memory"); return v;
}
__device__ __forceinline__ uint32_t xand(uint32_t a, uint32_t b, uint32_t m) {
    uint32_t r; asm("lop3.b32 %0,%1,%2,%3,0x42;" : "=r"(r) : "r"(a), "r"(b), "r"(m)); return r;
}
__device__ __forceinline__ uint32_t and3(uint32_t a, uint32_t b, uint32_t c) {
    uint32_t r; asm("lop3.b32 %0,%1,%2,%3,0x80;" : "=r"(r) : "r"(a), "r"(b), "r"(c)); return r;
}
__device__ __forceinline__ uint32_t settag(float v, uint32_t tag) {
    uint32_t r; asm("lop3.b32 %0,%1,0xfffffffe,%2,0xea;" : "=r"(r) : "r"(__float_as_uint(v)), "r"(tag)); return r;
}
__device__ __forceinline__ float rcp_fast(float x) { float r; asm("rcp.approx.ftz.f32 %0,%1;" : "=f"(r) : "f"(x)); return r; }
__device__ __forceinline__ void sts64f(uint32_t a, float x, float y) { asm volatile("st.shared.v2.f32 [%0],{%1,%2};" ::"r"(a), "f"(x), "f"(y) : "memory"); }

__device__ __forceinline__ uint32_t near_parity(uint8_t* blk, int cta) {
    uint32_t best[2] = {~0u, ~0u};
#pragma unroll
    for (int p = 0; p < 4; p++) *reinterpret_cast<uint4*>(blk + 0xE000 + (p >> 1) * 4096 + (cta & 31) * 128 + (p & 1) * 16) = make_uint4(0, 0, 0, 0);
    for (int r = 0; r < 4; r++)
#pragma unroll
        for (int p = 0; p < 2; p++) {
            uint8_t* a = blk + (0xF000 ^ (p << 12)) + (cta & 31) * 128;
            uint32_t v, t1 = 0;
            const uint32_t t0 = clk32();
            asm volatile("atom.relaxed.gpu.global.add.u32 %0,[%1],1;" : "=r"(v) : "l"(a) : "memory");
            asm volatile("{.reg .pred p; setp.ne.u32 p,%1,0x7fffffff; @p mov.u32 %0,%%clock;}" : "+r"(t1) : "r"(v) : "memory");
            best[p] = min(best[p], t1 - t0);
        }
    return best[0] <= best[1] ? 0u : 1u;
}

template <int GRP>
__device__ __forceinline__ void xfinish(uint32_t sxa, uint32_t vaa, uint32_t vma, uint32_t st_w, uint32_t st_r, uint8_t* dst, int g, int t, int nbar) {
    constexpr int NB = GRP + 2;
    constexpr bool needB = (GRP >= 2);
    const float sc = 0.08838834764831845f * 1.4426950408889634f;
    bar_sync(BAR_A, nbar);
    float2 v[6];
#pragma unroll
    for (int b = 0; b < NB + 1; b++) v[b] = lds64f(sxa + b * 32);
    uint32_t f0[4], f1[4];
    ldsm4(f0, vma);
    v[1].x += v[0].x; v[1].y += v[0].y;
    if (2 * t > g) v[NB].x = -INFINITY;
    if (2 * t + 1 > g) v[NB].y = -INFINITY;
    float mx = fmaxf(v[1].x, v[1].y);
#pragma unroll
    for (int b = 2; b < NB + 1; b++) mx = fmaxf(mx, fmaxf(v[b].x, v[b].y));
    mx = fmaxf(mx, __shfl_xor_sync(~0u, mx, 1));
    mx = fmaxf(mx, __shfl_xor_sync(~0u, mx, 2));
    mx *= sc;
    uint32_t pk[5];
    float sum = 0.f;
#pragma unroll
    for (int b = 0; b < 5; b++) {
        if (b < NB) {
            float p0 = ex2(fmaf(v[b + 1].x, sc, -mx)), p1 = ex2(fmaf(v[b + 1].y, sc, -mx));
            sum += p0 + p1;
            pk[b] = pack_bf16(p0, p1);
        } else pk[b] = 0u;
    }
    float o[2][4] = {{0.f, 0.f, 0.f, 0.f}, {0.f, 0.f, 0.f, 0.f}};
    ldsm4(f1, vaa);
    mma8(o[0], f0[0], f0[1], pk[0]);
    mma8(o[1], f0[2], f0[3], pk[0]);
    ldsm4(f0, vaa + 256);
    sum += __shfl_xor_sync(~0u, sum, 1);
    mma16(o[0], f1[0], f1[1], f1[2], f1[3], pk[1], pk[2]);
    if (needB) ldsm4(f1, vaa + 4096);
    mma16(o[1], f0[0], f0[1], f0[2], f0[3], pk[1], pk[2]);
    if (needB) ldsm4(f0, vaa + 4096 + 256);
    sum += __shfl_xor_sync(~0u, sum, 2);
    if (needB) {
        mma16(o[0], f1[0], f1[1], f1[2], f1[3], pk[3], pk[4]);
        mma16(o[1], f0[0], f0[1], f0[2], f0[3], pk[3], pk[4]);
    }
    const float s0 = __shfl_sync(~0u, sum, 8 * t), s1 = __shfl_sync(~0u, sum, 8 * t + 4);
    const float i0 = rcp_fast(s0), i1 = rcp_fast(s1);
    stsm4t(st_w, pack_bf16(o[0][0] * i0, o[0][1] * i1), pack_bf16(o[0][2] * i0, o[0][3] * i1),
           pack_bf16(o[1][0] * i0, o[1][1] * i1), pack_bf16(o[1][2] * i0, o[1][3] * i1));
    __syncwarp();
    uint4 val = lds128(st_r);
    *reinterpret_cast<uint4*>(dst + GRP * 1024) = val;
}

__device__ __forceinline__ void xrest(uint32_t sb, uint32_t xs, uint32_t mb, int c, int h, int s, int w, int lane, int wg) {
    const int g = lane >> 2, t = lane & 3, m = lane >> 3, r = lane & 7;
    const uint32_t sxa = sb + SM_SXX + (g * SXR + 2 * t) * 4;
    const uint32_t vaa = xs + 16384 + (m >> 1) * 2048 + (32 * w + 8 * (m & 1) + r) * 16;
    const uint32_t vma = mb + 4096 + (32 * w + lane) * 16;
    const uint32_t st_w = sb + SM_OX + w * 512 + r * 64 + ((m ^ ((r >> 1) & 3)) << 4);
    const uint32_t st_r = sb + SM_OX + w * 512 + g * 64 + ((t ^ ((g >> 1) & 3)) << 4);
    uint8_t* dst = g_ox + (size_t)((s >> 2) * 64 + 2 * h + (w >> 1)) * 16384 + ((s & 3) * 32 + g) * 128 + ((((w & 1) * 4 + t) ^ g) << 4);
    if (wg == 0) xfinish<0>(sxa, vaa, vma, st_w + 2048, st_r + 2048, dst, g, t, 256);
    else if (c == 2) xfinish<1>(sxa + 8 * SXR * 4, vaa, vma, st_w, st_r, dst, g, t, 256);
    else if (c == 0) xfinish<3>(sxa + 8 * SXR * 4, vaa, vma, st_w, st_r, dst, g, t, 128);
    else xfinish<2>(sxa, vaa, vma, st_w, st_r, dst, g, t, 128);
}

__device__ __forceinline__ void xattn(uint32_t sb, uint32_t xs, uint32_t mb, uint32_t barq, uint32_t phq, int c, int h, int s, int w, int lane, int& dead) {
    const int g = lane >> 2, t = lane & 3, m = lane >> 3, r = lane & 7;
    if (w < 2) {
        const int kt = (c == 2) ? 0 : w, grp = (c == 2) ? w : 3 - c;
        const uint32_t kb = xs + 8192 + (2 * kt + (m & 1)) * 2048 + (8 * (m >> 1) + r) * 16;
        const uint32_t qb = xs + grp * 2048 + lane * 16;
        float c0[4] = {0.f, 0.f, 0.f, 0.f}, c1[4] = {0.f, 0.f, 0.f, 0.f};
#pragma unroll
        for (int j = 0; j < 4; j++) {
            uint32_t q[4], a[4], b[4];
            ldsm4t(q, qb + j * 512);
            ldsm4t(a, kb + j * 512);
            ldsm4t(b, kb + j * 512 + 256);
            mma16(c0, a[0], a[1], a[2], a[3], q[0], q[1]);
            mma16(c1, b[0], b[1], b[2], b[3], q[2], q[3]);
        }
        const uint32_t p = sb + SM_SXX + (((grp & 1) * 8 + 2 * t) * SXR + 16 + 16 * kt + g) * 4;
        sts32f(p, c0[0] + c1[0]);
        sts32f(p + SXR * 4, c0[1] + c1[1]);
        sts32f(p + 32, c0[2] + c1[2]);
        sts32f(p + SXR * 4 + 32, c0[3] + c1[3]);
        mbar_wait(barq, phq, dead);
    } else {
        const uint4 at = lds128(sb + SM_AUX + (128 + w * 32 + lane) * 16);
        const uint32_t qa = mb + at.y, ka = mb + at.w, sxw = at.z;
        mbar_wait(barq, phq, dead);
        uint32_t a[2][4];
        {
            uint32_t q[2][4];
            float c0[4] = {0.f, 0.f, 0.f, 0.f}, c1[4] = {0.f, 0.f, 0.f, 0.f};
            ldsm4t(q[0], qa); ldsm4t(a[0], ka); ldsm4t(q[1], qa + 512); ldsm4t(a[1], ka + 512);
            mma16(c0, a[0][0], a[0][1], a[0][2], a[0][3], q[0][0], q[0][1]);
            mma16(c1, a[0][0], a[0][1], a[0][2], a[0][3], q[0][2], q[0][3]);
            mma16(c0, a[1][0], a[1][1], a[1][2], a[1][3], q[1][0], q[1][1]);
            mma16(c1, a[1][0], a[1][1], a[1][2], a[1][3], q[1][2], q[1][3]);
            sts32f(sxw, c0[0] + c1[2]);
            sts32f(sxw + SMR * 4, c0[1] + c1[3]);
            if (s < NSEG - 1) bar_arrive(BAR_S, 320);
        }
        uint32_t qx[4][4];
        const uint32_t base = xs + ((c == 2 ? 0 : 2) + (m & 1)) * 2048 + ((w - 2) * 64 + 8 * (m >> 1) + r) * 16;
#pragma unroll
        for (int j = 0; j < 4; j++) ldsm4t(qx[j], base + j * 256);
        float c2[4] = {0.f, 0.f, 0.f, 0.f}, c3[4] = {0.f, 0.f, 0.f, 0.f};
#pragma unroll
        for (int j = 0; j < 2; j++) {
            mma16(c2, qx[2 * j][0], qx[2 * j][1], qx[2 * j][2], qx[2 * j][3], a[j][0], a[j][1]);
            mma16(c3, qx[2 * j + 1][0], qx[2 * j + 1][1], qx[2 * j + 1][2], qx[2 * j + 1][3], a[j][2], a[j][3]);
        }
        const uint32_t sxx = sb + SM_SXX + (g * SXR + 8 * (w - 2) + 2 * t) * 4;
        sts64f(sxx, c2[0] + c3[0], c2[1] + c3[1]);
        sts64f(sxx + 8 * SXR * 4, c2[2] + c3[2], c2[3] + c3[3]);
    }
    xrest(sb, xs, mb, c, h, s, w, lane, 1);
}

#define SHIP_DELAY 100
#define W_PACE 1400
#define REGS_A 176
#define DELAY1 380
#define DELAY2 280

__device__ __forceinline__ void st_relaxed64(void* p, uint32_t lo, uint32_t hi) {
    asm volatile("{.reg .b64 v; mov.b64 v,{%1,%2}; st.relaxed.gpu.global.b64 [%0],v;}" ::"l"(p), "r"(lo), "r"(hi) : "memory");
}
__device__ __forceinline__ uint2 ld_relaxed64(const void* p) {
    uint2 v;
    asm volatile("{.reg .b64 v; ld.relaxed.gpu.global.b64 v,[%2]; mov.b64 {%0,%1},v;}" : "=r"(v.x), "=r"(v.y) : "l"(p) : "memory");
    return v;
}
__device__ __forceinline__ void sts32(uint32_t a, uint32_t v) { asm volatile("st.shared.u32 [%0],%1;" ::"r"(a), "r"(v) : "memory"); }

__global__ void __cluster_dims__(3, 1, 1) __launch_bounds__(384, 1)
k_chain(const __grid_constant__ CUtensorMap tmWq, const __grid_constant__ CUtensorMap tmWk, const __grid_constant__ CUtensorMap tmWv,
        const __grid_constant__ CUtensorMap tmWo, const __nv_bfloat16* __restrict__ x, const __nv_bfloat16* __restrict__ mem0,
        uint8_t* __restrict__ xb) {
    extern __shared__ __align__(1024) uint8_t smem[];
    const uint32_t sb = smem_u32(smem);
    const int tid = threadIdx.x, lane = tid & 31;
    const int warp = __shfl_sync(~0u, tid >> 5, 0);
    const int c = blockIdx.x % 3, h = blockIdx.x / 3;
    const uint32_t bar_qm = sb + SM_BAR, bar_x = sb + SM_BAR + 24, bar_xn = sb + SM_BAR + 48, bar_xf = sb + SM_BAR + 64, bar_w = sb + SM_BAR + 72;
    int dead = 0;

    pdl_launch();
    {
        if (tid == 0) {
            for (int i = 0; i < 11; i++) mbar_init(bar_qm + 8 * i, i < 3 ? 9 : (i == 8 ? 24 : 1));
            asm volatile("fence.mbarrier_init.release.cluster;" ::: "memory");
        }
        const int r0 = warp == 11 ? blockIdx.x : 96 + blockIdx.x * 11 + warp, r1 = warp == 11 ? SEQ : r0 + 1056;
        uint4 xr0[3], xr1[3];
        ln_load(xr0, x, r0, lane);
        ln_load(xr1, x, r1, lane);
        uint4 m0[5];
#pragma unroll
        for (int i = 0; i < 5; i++) {
            m0[i] = make_uint4(0, 0, 0, 0);
            if (warp >= 8 && tid - 256 + i * 128 < 576)
                asm volatile("ld.global.nc.v4.u32 {%0,%1,%2,%3},[%4];" : "=r"(m0[i].x), "=r"(m0[i].y), "=r"(m0[i].z), "=r"(m0[i].w)
                             : "l"(reinterpret_cast<const uint4*>(mem0) + tid - 256 + i * 128));
        }
        __syncthreads();
        if (warp == 8) PSTAMP(14);
        if (tid == 0) {
            asm volatile("{.reg .pred p; setp.eq.u32 p,%0,0x7fc1a5a5; @p nanosleep.u32 1;}" ::"r"(xr0[0].x ^ xr1[1].y) : "memory");
            mbar_expect_tx(bar_w + 8, 49152);
            for (int i = 0; i < 6; i++)
                tma2d(sb + (i < 4 ? SM_XN + i * 8192 : SM_TAB + (i - 4) * 8192), &tmWo, c * 192 + (i >> 1) * 64, h * DH + (i & 1) * 64, bar_w + 8);
            const CUtensorMap* tw = c == 0 ? &tmWq : (c == 1 ? &tmWk : &tmWv);
            mbar_expect_tx(bar_w, 147456);
            const uint32_t t0 = clk32();
            for (int i = 0; i < 6; i++) {
                while ((int)(clk32() - t0) < i * W_PACE);
                tma2d(sb + SM_STG_W + (i & 1) * 73728 + (i >> 1) * 24576, tw, h * DH + (i & 1) * 64, (i >> 1) * 192, bar_w);
            }
        }
        ln_row(xr0, r0, lane);
        if (warp == 11) {
            asm volatile("fence.acq_rel.gpu;" ::: "memory");
            __syncwarp();
            if (lane == 0) red_add1(g_tab + 100);
        }
        if (warp >= 8) {
#pragma unroll
            for (int i = 0; i < 5; i++) {
                const int ci = tid - 256 + i * 128;
                if (ci < 576) {
                    const uint32_t wv[4] = {m0[i].x, m0[i].y, m0[i].z, m0[i].w};
                    uint16_t* dst = reinterpret_cast<uint16_t*>(smem + SM_MEMT + (ci % 72) * 128 + (ci / 72) * 2);
#pragma unroll
                    for (int j = 0; j < 4; j++) { dst[16 * j] = (uint16_t)wv[j]; dst[16 * j + 8] = (uint16_t)(wv[j] >> 16); }
                }
            }
        }
        if (warp == 8) PSTAMP(15);
        if (r1 < SEQ) ln_row(xr1, r1, lane);
        if (warp < 8) {
            uint8_t* blk = xb + (size_t)blockIdx.x * 65536;
            uint8_t* c2b = xb + (size_t)96 * 65536;
            for (int i = tid; i < 1024; i += 256) *reinterpret_cast<uint4*>(blk + (i >> 9) * 32768 + (i & 511) * 16) = make_uint4(0, 0, 0, 0);
            if (tid < 48) {
                const int o = blockIdx.x * 96 + (tid % 6) * 16, v = tid / 6;
                *reinterpret_cast<uint4*>(c2b + (v >> 2) * 65536 + (v & 3) * 4096 + (o >> 12) * 16384 + (o & 4095)) = make_uint4(0, 0, 0, 0);
            }
        }
        if (warp < 8) bar_arrive(BAR_QD, 384);
        PSTAMP(4);
    }
    auto ship_x = [&](int sl) {
        const uint32_t src = sb + SM_X + sl * 24576 + c * 8192, bx = bar_x + sl * 8;
        const uint32_t p1 = (c + 1) % 3, p2 = (c + 2) % 3;
        bulk_s2s(mapa(src, p1), src, 8192, mapa(bx, p1));
        bulk_s2s(mapa(src, p2), src, 8192, mapa(bx, p2));
        mbar_expect_tx(bx, 16384);
    };
    auto load_xn = [&](int seg) {
        const int b = seg & 1;
        mbar_expect_tx(bar_xn + 8 * b, XN_SEG_BYTES);
        bulk_g2s_mc(sb + SM_XN + b * XN_SEG_BYTES + c * 12288, g_xn + (size_t)seg * XN_SEG_BYTES + c * 12288, 12288, bar_xn + 8 * b, 7);
    };

    if (warp < 8) {
        if (REGS_A > 168) asm volatile("setmaxnreg.inc.sync.aligned.u32 %0;" ::"n"(REGS_A));
        mbar_wait(bar_w, 0, dead);
        PSTAMP(10);
        uint32_t W[NREG_K][4];
        {
            const int m = lane >> 3, r = lane & 7;
            const uint32_t wa = sb + SM_STG_W + (warp >> 2) * 73728 + (8 * (m >> 1) + r) * 128 + (((2 * (warp & 3) + (m & 1)) ^ r) << 4);
#pragma unroll
            for (int j = 0; j < 36; j++) {
                if (j < NREG_K) ldsm4t(W[j], wa + j * 2048);
                else {
                    uint32_t f[4];
                    ldsm4t(f, wa + j * 2048);
                    stsm4(sb + SM_WS + (j - NREG_K) * 4096 + (m >> 1) * 2048 + (2 * warp + (m & 1)) * 128 + r * 16, f[0], f[1], f[2], f[3]);
                }
            }
            fence_async();
        }
        bar_sync(BAR_A, 256);
        if (tid == 0) {
            int n = 0;
            while (ld_acquire1(g_tab + 100) < 96u) { if (++n > SPIN_LIMIT) { dead = 1; break; } }
            fence_async_g(); fence_async();
            mbar_expect_tx(bar_xn + 8, XN_SEG_BYTES);
            bulk_g2s(sb + SM_XN + XN_SEG_BYTES, g_xn + XN_SEG_BYTES, XN_SEG_BYTES, bar_xn + 8);
        }
        __syncwarp();
        asm volatile("barrier.cluster.arrive.relaxed.aligned;" ::: "memory");
        const uint32_t rb1 = mapa(sb, (c + 1) % 3), rb2 = mapa(sb, (c + 2) % 3);
        int slot = 0, ph3 = 0;
        for (int s = -2; s < NSEG; s++) {
            const int sl = slot == 2 ? 0 : slot + 1;
            int lane;
            asm volatile("mov.u32 %0,%%laneid;" : "=r"(lane));
            if (s >= 0) {
                uint32_t WS[36 - NREG_K][4];
                {
                    const uint32_t a = sb + SM_WS + ((lane >> 4) & 1) * 2048 + (2 * warp + ((lane >> 3) & 1)) * 128 + (lane & 7) * 16;
#pragma unroll
                    for (int j = 0; j < 36 - NREG_K; j++) ldsm4(WS[j], a + j * 4096);
                }
                const uint32_t doff = SM_MB + c * 2048 + warp * 256 + lane * 4 + sl * 6144;
                const uint32_t ma = sb + SM_MEMT + lane * 16;
                bar_sync(BAR_MEM, 384);
                float a0[4] = {0.f, 0.f, 0.f, 0.f}, a1[4] = {0.f, 0.f, 0.f, 0.f}, a2[4] = {0.f, 0.f, 0.f, 0.f};
                uint32_t b[5][4];
                constexpr int J0 = NREG_K / 2;
                ldsm4t(b[0], ma + J0 * 512);
                ldsm4t(b[1], ma + ((J0 + 1) % 18) * 512);
                TSTAMP(0);
#pragma unroll
                for (int jj = 0; jj < 18; jj++) {
                    const int j = (jj + J0) % 18;
                    if (jj == 1) { ldsm4t(b[2], ma + ((J0 + 2) % 18) * 512); ldsm4t(b[3], ma + ((J0 + 3) % 18) * 512); }
                    if (jj >= 1 && jj + 3 < 18) ldsm4t(b[(jj + 3) % 5], ma + ((jj + 3 + J0) % 18) * 512);
                    const uint32_t(&bb)[4] = b[jj % 5];
                    float(&c0)[4] = (2 * jj) % 3 == 0 ? a0 : ((2 * jj) % 3 == 1 ? a1 : a2);
                    float(&c1)[4] = (2 * jj + 1) % 3 == 0 ? a0 : ((2 * jj + 1) % 3 == 1 ? a1 : a2);
                    if (2 * j < NREG_K) mma16(c0, W[2 * j][0], W[2 * j][1], W[2 * j][2], W[2 * j][3], bb[0], bb[1]);
                    else mma16(c0, WS[2 * j - NREG_K][0], WS[2 * j - NREG_K][1], WS[2 * j - NREG_K][2], WS[2 * j - NREG_K][3], bb[0], bb[1]);
                    if (2 * j + 1 < NREG_K) mma16(c1, W[2 * j + 1][0], W[2 * j + 1][1], W[2 * j + 1][2], W[2 * j + 1][3], bb[2], bb[3]);
                    else mma16(c1, WS[2 * j + 1 - NREG_K][0], WS[2 * j + 1 - NREG_K][1], WS[2 * j + 1 - NREG_K][2], WS[2 * j + 1 - NREG_K][3], bb[2], bb[3]);
                }
                const uint32_t w0 = pack_bf16(a0[0] + a1[0] + a2[0], a0[1] + a1[1] + a2[1]);
                const uint32_t w1 = pack_bf16(a0[2] + a1[2] + a2[2], a0[3] + a1[3] + a2[3]);
                const uint32_t boff = SM_BAR + sl * 8;
                st_async32(rb1 + doff, w0, rb1 + boff); st_async32(rb2 + doff, w0, rb2 + boff);
                st_async32(rb1 + doff + 128, w1, rb1 + boff); st_async32(rb2 + doff + 128, w1, rb2 + boff);
                sts32(sb + doff, w0); sts32(sb + doff + 128, w1);
                __syncwarp();
                if (lane == 0) mbar_arrive(sb + boff);
                if (s < NSEG - 1) bar_arrive(BAR_U, 384);
                TSTAMP(1);
            }
            const int sn = s + 2;
            const uint64_t desc0 = mk_desc(sb + SM_XN + (sn & 1) * XN_SEG_BYTES, 16, 1024);
            const uint64_t da = (uint64_t)(((sb + SM_WS + (warp >> 2) * 1024) & 0x3FFFF) >> 4) | (128ull << 16) | (8ull << 32);
            float acc[16];
            if (s >= 0) {
                mbar_wait(bar_x + sl * 8, ph3, dead);
                const uint32_t xs = sb + SM_X + sl * 24576, mb = sb + SM_MB + sl * 6144;
                if (warp < 4) {
                    if (s == NSEG - 1) {
                        if (c == 2) xrest(sb, xs, mb, c, h, s, warp, lane, 0);
                        bar_arrive(BAR_GO, 256);
                        break;
                    }
                    const uint4 at = lds128(sb + SM_AUX + (warp * 32 + lane) * 16);
                    const uint32_t qa = mb + at.y, sxw = at.z;
                    uint32_t kf[4][4];
#pragma unroll
                    for (int j = 0; j < 4; j++) ldsm4t(kf[j], xs + at.w + j * 256);
                    mbar_wait(bar_qm + sl * 8, ph3, dead);
                    uint32_t q[2][4];
                    ldsm4t(q[0], qa); ldsm4t(q[1], qa + 512);
                    float c0[4] = {0.f, 0.f, 0.f, 0.f}, c1[4] = {0.f, 0.f, 0.f, 0.f}, c2[4] = {0.f, 0.f, 0.f, 0.f}, c3[4] = {0.f, 0.f, 0.f, 0.f};
                    mma16(c0, kf[0][0], kf[0][1], kf[0][2], kf[0][3], q[0][0], q[0][1]);
                    mma16(c1, kf[1][0], kf[1][1], kf[1][2], kf[1][3], q[0][2], q[0][3]);
                    mma16(c2, kf[2][0], kf[2][1], kf[2][2], kf[2][3], q[1][0], q[1][1]);
                    mma16(c3, kf[3][0], kf[3][1], kf[3][2], kf[3][3], q[1][2], q[1][3]);
                    sts32f(sxw, (c0[0] + c1[0]) + (c2[0] + c3[0]));
                    sts32f(sxw + SMR * 4, (c0[1] + c1[1]) + (c2[1] + c3[1]));
                    sts32f(sxw + 64, (c0[2] + c1[2]) + (c2[2] + c3[2]));
                    sts32f(sxw + SMR * 4 + 64, (c0[3] + c1[3]) + (c2[3] + c3[3]));
                    bar_arrive(BAR_S, 320);
                    TSTAMP(2);
                    __syncwarp();
                    if (c == 2) xrest(sb, xs, mb, c, h, s, warp, lane, 0);
                    TSTAMP(5);
                } else {
                    xattn(sb, xs, mb, bar_qm + sl * 8, ph3, c, h, s, warp - 4, lane, dead);
                    TSTAMP(2);
                    if (s == NSEG - 1) {
                        bar_sync(BAR_GO, 256);
                        if (tid == 128) { asm volatile("fence.acq_rel.gpu;" ::: "memory"); red_add1(g_flag + 15 * 32 + FL_OX); }
                        break;
                    }
                }
                if ((s & 3) == 3) bar_arrive(BAR_OX, 288);
            } else mbar_wait(bar_xn + (sn & 1) * 8, 0, dead);
            asm volatile("{.reg .pred p; setp.ge.s32 p,%0,0; @p bar.sync %1,256;}" ::"r"(s), "r"(warp < 4 ? BAR_GO : BAR_GO2) : "memory");
#pragma unroll
            for (int i = 0; i < 16; i++) acc[i] = 0.f;
            {
                wg_fence();
#pragma unroll
                for (int j = 0; j < BULK1; j++) {
                    wgmma_n32_rs(acc, W[j], desc0 + (uint64_t)(((j >> 2) * 4096 + (j & 3) * 32) >> 4), j > 0);
                }
                wg_commit();
                wg_wait<0>();
            }
            asm volatile("{.reg .pred p; setp.ge.s32 p,%0,0; @p bar.sync %1,320;}" ::"r"(s), "r"(BAR_QD) : "memory");
            {
                wg_fence();
#pragma unroll
                for (int j = BULK1; j < NREG_K; j++) wgmma_n32_rs(acc, W[j], desc0 + (uint64_t)(((j >> 2) * 4096 + (j & 3) * 32) >> 4), j > 0);
#pragma unroll
                for (int j = NREG_K; j < 36; j++)
                    wgmma_n32_ss(acc, da + (uint64_t)((j - NREG_K) * 256), desc0 + (uint64_t)(((j >> 2) * 4096 + (j & 3) * 32) >> 4));
                wg_commit();
                wg_wait<0>();
            }
            if (s > -2 && lane < 3)
                asm volatile("mbarrier.arrive.relaxed.cluster.shared::cluster.b64 _,[%0];" ::"r"(mapa(bar_xf, lane)) : "memory");
            TSTAMP(3);
            {
                const uint32_t xo = sb + SM_X + slot * 24576 + c * 8192 + ((lane >> 4) & 1) * 2048 + (16 * warp + 8 * ((lane >> 3) & 1) + (lane & 7)) * 16;
                stsm4(xo, pack_bf16(acc[0], acc[1]), pack_bf16(acc[2], acc[3]), pack_bf16(acc[4], acc[5]), pack_bf16(acc[6], acc[7]));
                stsm4(xo + 4096, pack_bf16(acc[8], acc[9]), pack_bf16(acc[10], acc[11]), pack_bf16(acc[12], acc[13]), pack_bf16(acc[14], acc[15]));
                fence_async();
            }
            if (s == -2) {
                asm volatile("barrier.cluster.wait.acquire.aligned;" ::: "memory");
                bar_arrive(0, 288);
            }
            TSTAMP(4);
            if (s >= 0) { TFLUSH(); }
            if (sl == 2 && s >= 0) ph3 ^= 1;
            slot = sl;
        }
        cluster_sync();
    } else {
        if (REGS_A > 168) asm volatile("setmaxnreg.dec.sync.aligned.u32 %0;" ::"n"(504 - 2 * REGS_A));
        const int w = warp - 8, bt = tid - 256;
        const int cta = blockIdx.x;
        uint8_t* const c2b = xb + (size_t)96 * 65536;
        PSTAMP(11);
        asm volatile("barrier.cluster.arrive.relaxed.aligned;" ::: "memory");
        PSTAMP(12);
        PSTAMP(13);
        volatile uint32_t* sp = reinterpret_cast<volatile uint32_t*>(smem + SM_TIM + 900);
        if (bt == 32) sp[1] = near_parity(xb + (size_t)cta * 65536, cta);
        __syncwarp();
        mbar_wait(bar_w + 8, 0, dead);
        PSTAMP(6);
        uint32_t WO[3][8][4];
        {
            const int m = lane >> 3, r = lane & 7;
#pragma unroll
            for (int i = 0; i < 3; i++)
#pragma unroll
                for (int j = 0; j < 8; j++) {
                    const int k = 16 * j + 8 * (m >> 1) + r, ch = 2 * (3 * w + i) + (m & 1);
                    ldsm4t(WO[i][j], sb + (ch < 16 ? SM_XN + (ch >> 3) * 16384 : SM_TAB) + k * 128 + (((ch & 7) ^ r) << 4));
                }
        }
        bar_sync(BAR_QD, 384);
        {
            const int g = lane >> 2, t = lane & 3, m = lane >> 3, r = lane & 7;
            sts128(sb + SM_AUX + bt * 16, make_uint4(0, (w & 1) * 1024 + lane * 16,
                   sb + SM_SX + (2 * t * SMR + (1 + (w & 2)) * 16 + (g >> 1) * 4 + (w & 1) * 2 + (g & 1)) * 4,
                   8192 + ((w & 2) + (m & 1)) * 2048 + ((w & 1) * 64 + 8 * (m >> 1) + r) * 16));
            sts128(sb + SM_AUX + 2048 + bt * 16, make_uint4(0, (w & 1) * 1024 + ((((m & 1) << 1) | (m >> 1)) * 8 + r) * 16,
                   sb + SM_SX + (2 * t * SMR + (g >> 1) * 4 + (w & 1) * 2 + (g & 1)) * 4, 2048 + (w & 1) * 1024 + lane * 16));
        }
        bar_arrive(BAR_MEM, 384);
        if (lane == 0) {
            if (w == 0) {
                int n = 0;
                while (ld_acquire1(g_tab + 100) < 96u) { if (++n > SPIN_LIMIT) { dead = 1; break; } }
                fence_async_g(); fence_async();
                mbar_expect_tx(bar_xn, XN_SEG_BYTES);
                bulk_g2s(sb + SM_XN, g_xn, XN_SEG_BYTES, bar_xn);
            } else if (w == 1) {
                asm volatile("fence.acq_rel.gpu;" ::: "memory");
                st_relaxed1(g_tab + cta, 1u + sp[1]);
            } else sp[w] = near_parity(c2b + (w - 2) * 65536, cta);
        }
        __syncwarp();
        PSTAMP(7);
        asm volatile("barrier.cluster.wait.acquire.aligned;" ::: "memory");
        if (w == 0) {
            bar_sync(0, 288);
            PSTAMP(9);
            if (lane == 0) {
                fence_async_g();
                ship_x(0);
                mbar_wait(bar_x, 0, dead);
                load_xn(2);
            }
        } else {
            uint32_t tv;
            int n = 0;
            while ((tv = ld_acquire1(g_tab + bt - 32)) == 0u) { if (++n > SPIN_LIMIT) { dead = 1; break; } }
            reinterpret_cast<volatile uint8_t*>(smem + SM_TIM + 800)[bt - 32] = (uint8_t)(tv - 1);
        }
        dead = __any_sync(~0u, dead);
        bar_sync(BAR_B, 128);
        const uint32_t pinfo = __shfl_sync(~0u, sp[2] | (sp[3] << 1) | (sp[1] << 2), 0);
        if (bt == 0) fence_async_g();
        PSTAMP(5);
        for (int i = 0; i < 3; i++) {
            const int u = (c * 12 + w * 3 + i) * 4 + (lane >> 3), d = u < 96 ? u : 2 * (u - 96);
            reinterpret_cast<volatile uint32_t*>(smem + SM_TAB)[bt * 4 + i] =
                d * 65536 + (reinterpret_cast<volatile uint8_t*>(smem + SM_TIM + 800)[d] & 1) * 4096 + (u < 96 ? 0 : 2048) + h * 64 + (lane & 7) * 8;
        }
        reinterpret_cast<volatile uint32_t*>(smem + SM_TAB)[bt * 4 + 3] = sb + SM_SX + ((lane >> 2) * SMR + 4 * (lane & 3)) * 4;
        PSTAMP(8);
        __syncwarp();
        const float sc = 0.08838834764831845f * 1.4426950408889634f;
        int slot = 0, ph3 = 0;
        for (int s = 0; s < NSEG; s++) {
            int lane;
            asm volatile("mov.u32 %0,%%laneid;" : "=r"(lane));
            const int g = lane >> 2, t = lane & 3, m = lane >> 3, r = lane & 7, bt = w * 32 + lane;
            const uint32_t xs = sb + SM_X + slot * 24576;
            const uint32_t mb = sb + SM_MB + slot * 6144;
            if (bt == 64) mbar_expect_tx(bar_qm + slot * 8, 4096);
            if (s == NSEG - 1) break;
            const uint32_t tag = ((s >> 1) & 1) ^ 1;
            const uint4 tab = lds128(sb + SM_TAB + bt * 16);
            const uint32_t sxr = tab.w;
            const uint32_t l16 = sb + lane * 16;
            const uint32_t one = 0x3f803f80u;
            uint32_t va[2][2][4], vmm[4];
            mbar_wait(bar_x + slot * 8, ph3, dead);
            if (s + 2 < NSEG) mbar_wait(bar_xn + (s & 1) * 8, ((s + 2) >> 1) & 1, dead);
            bar_sync(BAR_U, 384);
            if (bt == 32 && s + 3 < NSEG) {
                mbar_wait(bar_xf, s & 1, dead);
                load_xn(s + 3);
            }
            __syncwarp();
            const uint32_t vaa = xs + 16384 + (m >> 1) * 2048 + (32 * w + 8 * (m & 1) + r) * 16;
            ldsm4(va[0][0], vaa); ldsm4(va[1][0], vaa + 256);
            ldsm4(va[0][1], vaa + 4096); ldsm4(va[1][1], vaa + 4096 + 256);
            TSTAMP(1);
            mbar_wait(bar_qm + slot * 8, ph3, dead);
            ldsm4(vmm, mb + 4096 + bt * 16);
            TSTAMP(2);
            bar_sync(BAR_S, 320);
            float2 v[5];
            {
                uint4 u[5];
#pragma unroll
                for (int b = 0; b < 5; b++) u[b] = lds128(sxr + b * 64);
#pragma unroll
                for (int b = 0; b < 5; b++) v[b] = make_float2(__uint_as_float(u[b].x) + __uint_as_float(u[b].z), __uint_as_float(u[b].y) + __uint_as_float(u[b].w));
            }
            TSTAMP(3);
            float mx = fmaxf(fmaxf(fmaxf(v[4].x, v[4].y), fmaxf(v[1].x, v[1].y)), fmaxf(fmaxf(v[2].x, v[2].y), fmaxf(v[3].x, v[3].y)));
            mx = fmaxf(mx, fmaxf(v[0].x, v[0].y));
            mx = fmaxf(mx, __shfl_xor_sync(~0u, mx, 1));
            mx = fmaxf(mx, __shfl_xor_sync(~0u, mx, 2));
            mx *= sc;
            float o[2][4] = {{0.f, 0.f, 0.f, 0.f}, {0.f, 0.f, 0.f, 0.f}}, rs[4] = {0.f, 0.f, 0.f, 0.f};
            {
                uint32_t pk[5];
#pragma unroll
                for (int b = 0; b < 5; b++) pk[b] = pack_bf16(ex2(fmaf(v[b].x, sc, -mx)), ex2(fmaf(v[b].y, sc, -mx)));
                mma8(o[0], vmm[0], vmm[1], pk[0]);
                mma8(o[1], vmm[2], vmm[3], pk[0]);
                mma8(rs, one, one, pk[0]);
                mma16(o[0], va[0][0][0], va[0][0][1], va[0][0][2], va[0][0][3], pk[1], pk[2]);
                mma16(o[1], va[1][0][0], va[1][0][1], va[1][0][2], va[1][0][3], pk[1], pk[2]);
                mma16(rs, one, one, one, one, pk[1], pk[2]);
                mma16(o[0], va[0][1][0], va[0][1][1], va[0][1][2], va[0][1][3], pk[3], pk[4]);
                mma16(o[1], va[1][1][0], va[1][1][1], va[1][1][2], va[1][1][3], pk[3], pk[4]);
                mma16(rs, one, one, one, one, pk[3], pk[4]);
                stsm4(l16 + SM_OT + w * 512, pack_bf16(o[0][0], o[0][1]), pack_bf16(o[0][2], o[0][3]), pack_bf16(o[1][0], o[1][1]), pack_bf16(o[1][2], o[1][3]));
                TSTAMP(4);
                bar_sync(BAR_B, 128);
            }
            uint32_t ob[4][4];
#pragma unroll
            for (int j = 0; j < 4; j++) ldsm4t(ob[j], l16 + SM_OT + j * 512);
            TSTAMP(5);
            {
                float d[3][2][4];
#pragma unroll
                for (int i = 0; i < 3; i++)
#pragma unroll
                    for (int k = 0; k < 4; k++) d[i][0][k] = d[i][1][k] = 0.f;
#pragma unroll
                for (int j = 0; j < 8; j++)
#pragma unroll
                    for (int i = 0; i < 3; i++)
                        mma16(d[i][j & 1], WO[i][j][0], WO[i][j][1], WO[i][j][2], WO[i][j][3], ob[j >> 1][(j & 1) * 2], ob[j >> 1][(j & 1) * 2 + 1]);
                const float i0 = rcp_fast(rs[0]), i1 = rcp_fast(rs[1]);
                uint8_t* const xs1 = xb + (s & 1) * 32768;
                const uint32_t off[3] = {tab.x, tab.y, tab.z};
#pragma unroll
                for (int i = 0; i < 3; i++)
                    st_relaxed64(xs1 + off[i], settag(__uint_as_float(pack_bf16((d[i][0][0] + d[i][1][0]) * i0, (d[i][0][1] + d[i][1][1]) * i1)), tag),
                                 pack_bf16((d[i][0][2] + d[i][1][2]) * i0, (d[i][0][3] + d[i][1][3]) * i1));
            }
            const uint32_t t_st = clk32();
            TSTAMP(6);
            const bool owner = w == 0 || (w == 1 && !(cta & 1));
            const uint8_t* src = xb + (cta * 65536 + (pinfo & 4u) * 1024 + (s & 1) * 32768 + (w & 1) * 2048) + (uint32_t)((g >> 2) * 256 + t * 64 + (g & 3) * 16);
            bar_arrive(BAR_GO, 256);
            bar_arrive(BAR_GO2, 256);
            if (w == 2) while ((int)(clk32() - t_st) < SHIP_DELAY);
            if (bt == 64) {
                ship_x(slot == 2 ? 0 : slot + 1);
            }
            __syncwarp();
            const uint8_t* src2 = c2b + (((s >> 1) & 1) * 65536 + ((s & 1) * 0x3000 ^ (((pinfo >> ((s >> 1) & 1)) & 1) << 12))) + (uint32_t)(bt * 16);
            const uint32_t mt = sb + SM_MEMT + bt * 16;
            uint32_t t_pub = 0;
            if (owner) {
                const int u = w == 0 ? cta : 96 + (cta >> 1), o = (u >> 2) * 256 + (u & 3) * 32;
                const uint32_t o_pub = (o >> 12) * 16384 + (o & 4095) + (g >> 2) * 128 + ((g & 3) * 2 + (t & 1)) * 4 + (t >> 1) * 0x1000;
                const uint32_t msk = tag ^ 1u;
                int n = 0;
                uint4 v2[4];
                auto ld2 = [&](const uint8_t* a) {
                    uint4 v;
                    asm volatile("{.reg .b64 a,b; ld.relaxed.gpu.global.v2.b64 {a,b},[%4]; mov.b64 {%0,%1},a; mov.b64 {%2,%3},b;}"
                                 : "=r"(v.x), "=r"(v.y), "=r"(v.z), "=r"(v.w) : "l"(a) : "memory");
                    return v;
                };
                while ((int)(clk32() - t_st) < DELAY1);
#pragma unroll
                for (int i = 0; i < 4; i++) v2[i] = ld2(src + i * 512);
                TSTAMP(7);
                const uint32_t sel = (g & 1) ? 0x3f800000u : 0x00003f80u, s0 = (g & 2) ? 0u : sel, s1 = (g & 2) ? sel : 0u;
                uint8_t* const pub = c2b + (((s >> 1) & 1) * 65536 + (s & 1) * 0x2000) + o_pub;
                while (!__all_sync(~0u, (and3(xand(v2[0].x, v2[0].z, msk), xand(v2[1].x, v2[1].z, msk), xand(v2[2].x, v2[2].z, msk) & xand(v2[3].x, v2[3].z, msk)) | dead) & 1u)) {
#pragma unroll
                    for (int i = 0; i < 4; i++) if (!(xand(v2[i].x, v2[i].z, msk) & 1u)) v2[i] = ld2(src + i * 512);
                    if (++n > SPIN_LIMIT) dead = 1;
                }
                float r0[4] = {0.f, 0.f, 0.f, 0.f}, r1[4] = {0.f, 0.f, 0.f, 0.f}, r2[4] = {0.f, 0.f, 0.f, 0.f}, r3[4] = {0.f, 0.f, 0.f, 0.f};
                mma16(r0, v2[0].x, v2[0].y, v2[0].z, v2[0].w, s0, s1);
                mma16(r1, v2[1].x, v2[1].y, v2[1].z, v2[1].w, s0, s1);
                mma16(r2, v2[2].x, v2[2].y, v2[2].z, v2[2].w, s0, s1);
                mma16(r3, v2[3].x, v2[3].y, v2[3].z, v2[3].w, s0, s1);
                float f[4];
#pragma unroll
                for (int k = 0; k < 4; k++) f[k] = (r0[k] + r1[k]) + (r2[k] + r3[k]);
                const bool hi = lane & 16;
                const float k0 = (hi ? f[2] : f[0]) + __shfl_xor_sync(~0u, hi ? f[0] : f[2], 16);
                const float k1 = (hi ? f[3] : f[1]) + __shfl_xor_sync(~0u, hi ? f[1] : f[3], 16);
                uint32_t word = pack_bf16(k0, k1);
                if (word == 0u) word = 0x80000000u;
                st_relaxed1(pub, word);
                t_pub = clk32();
                st_relaxed1(c2b + ((((s - 1) >> 1) & 1) * 65536 + ((s - 1) & 1) * 0x2000) + o_pub, 0u);
            }
            if (w < 2) bar_arrive(BAR_QD, 320);
            {
                bar_sync(BAR_B, 128);
                asm volatile("{.reg .pred p; .reg .u32 x; ld.shared.u32 x,[%1]; setp.ne.u32 p,x,0x7fc1a5a5; @p mov.u32 %0,%%clock;}" : "+r"(t_pub) : "r"(sb + SM_TAB) : "memory");
            }
            TSTAMP(8);
            {
                uint4 v4[5];
                uint32_t ok[5];
                v4[4] = make_uint4(1, 1, 1, 1);
                while ((int)(clk32() - t_pub) < DELAY2);
#pragma unroll
                for (int i = 0; i < 4; i++) v4[i] = ld_relaxed4(src2 + (i & 1) * 2048 + (i >> 1) * 16384);
                if (w >= 2) v4[4] = ld_relaxed4(src2 + 32768 - 1024);
                int n = 0;
                while (true) {
#pragma unroll
                    for (int i = 0; i < 4; i++) sts128(mt + i * 2048, v4[i]);
                    if (w >= 2) sts128(mt + 8192 - 1024, v4[4]);
#pragma unroll
                    for (int i = 0; i < 5; i++) ok[i] = min(__vimin3_u32(v4[i].x, v4[i].y, v4[i].z), v4[i].w);
                    const uint32_t all = min(__vimin3_u32(ok[0], ok[1], ok[2]), min(ok[3], ok[4]));
                    if (__all_sync(~0u, (all | dead) != 0)) break;
#pragma unroll
                    for (int i = 0; i < 5; i++) if (!ok[i]) v4[i] = ld_relaxed4(src2 + (i & 1) * 2048 + (i >> 1) * 16384 - (i == 4 ? 1024 : 0));
                    if (++n > SPIN_LIMIT) dead = 1;
                }
                bar_arrive(BAR_MEM, 384);
            }
            TSTAMP(9);
            if (w == 3 && (s & 3) == 3) {
                bar_sync(BAR_OX, 288);
                asm volatile("fence.acq_rel.gpu;" ::: "memory");
                if (lane == 0) red_add1(g_flag + (s >> 2) * 32 + FL_OX);
            }
            TSTAMP(10);
            TFLUSH();
            if (slot == 2) { slot = 0; ph3 ^= 1; } else slot++;
        }
        if (bt == 0) { g_tab[cta] = 0u; if (cta == 0) g_tab[100] = 0u; }
        cluster_sync();
    }
}

constexpr int G_ST = 4;
constexpr int G_STAGE = 16384 + 24576;
constexpr int T_STG = G_ST * G_STAGE;
constexpr int AUXB = 9216 + 1536;
constexpr int T_AUX0 = T_STG + 49152;
constexpr int T_B2 = T_AUX0 + AUXB;
constexpr int T_BAR = T_B2 + 2304;
constexpr int T_SMEM = T_BAR + 256 + 1024;
static_assert(T_SMEM <= 232448, "smem");
constexpr int NINIT = 36;
#define KW2 11
#define KW4 13
#define KF2 9
#define KF4 12
#define SCHED_AHEAD 1
#define KSW_S 10
#define KSF_S 11
#define T_START_DELAY 18000
#define POLL_NS 100
#define FINAL_FIRST 1
#define SM0 15
#define SM1 15
#define SM2 15
__host__ __device__ constexpr bool small_t(int type, int rb) { return rb >= (type == 0 ? SM0 : (type == 1 ? SM1 : SM2)); }
__host__ __device__ constexpr int ks_w(int rb) { return small_t(0, rb) ? KSW_S : (rb == 0 ? 8 : (rb < KW2 ? 2 : (rb < KW4 ? 4 : 8))); }
__host__ __device__ constexpr int ks_f(int rb) { return small_t(2, rb) ? KSF_S : (rb < KF2 ? 2 : (rb < KF4 ? 4 : 8)); }
__host__ __device__ constexpr int ntile(int type, int rb) { return small_t(type, rb) ? 9 : 3; }
__host__ __device__ constexpr int kpart(int total, int ks) { return ks == 2 ? total / 2 - 4 : (ks == 4 ? total / 4 - 2 : (ks == 1 ? total : (ks <= 9 ? total / ks - 1 : total / ks))); }

__device__ __forceinline__ void wgmma_ss(float (&d)[32], uint64_t da, uint64_t db, int scale_d) {
    asm volatile("{.reg .pred p; setp.ne.b32 p,%34,0;\n"
                 "wgmma.mma_async.sync.aligned.m64n64k16.f32.bf16.bf16 {"
                 "%0,%1,%2,%3,%4,%5,%6,%7,%8,%9,%10,%11,%12,%13,%14,%15,%16,%17,%18,%19,%20,%21,%22,%23,"
                 "%24,%25,%26,%27,%28,%29,%30,%31},%32,%33,p,1,1,0,1;}"
                 : "+f"(d[0]), "+f"(d[1]), "+f"(d[2]), "+f"(d[3]), "+f"(d[4]), "+f"(d[5]), "+f"(d[6]), "+f"(d[7]),
                   "+f"(d[8]), "+f"(d[9]), "+f"(d[10]), "+f"(d[11]), "+f"(d[12]), "+f"(d[13]), "+f"(d[14]), "+f"(d[15]),
                   "+f"(d[16]), "+f"(d[17]), "+f"(d[18]), "+f"(d[19]), "+f"(d[20]), "+f"(d[21]), "+f"(d[22]), "+f"(d[23]),
                   "+f"(d[24]), "+f"(d[25]), "+f"(d[26]), "+f"(d[27]), "+f"(d[28]), "+f"(d[29]), "+f"(d[30]), "+f"(d[31])
                 : "l"(da), "l"(db), "r"(scale_d));
}
__device__ __forceinline__ void wgmma_ss(float (&d)[96], uint64_t da, uint64_t db, int scale_d) {
    asm volatile("{.reg .pred p; setp.ne.b32 p,%98,0;\n"
                 "wgmma.mma_async.sync.aligned.m64n192k16.f32.bf16.bf16 {"
                 "%0,%1,%2,%3,%4,%5,%6,%7,%8,%9,%10,%11,%12,%13,%14,%15,%16,%17,%18,%19,%20,%21,%22,%23,"
                 "%24,%25,%26,%27,%28,%29,%30,%31,%32,%33,%34,%35,%36,%37,%38,%39,%40,%41,%42,%43,%44,%45,%46,%47,"
                 "%48,%49,%50,%51,%52,%53,%54,%55,%56,%57,%58,%59,%60,%61,%62,%63,%64,%65,%66,%67,%68,%69,%70,%71,"
                 "%72,%73,%74,%75,%76,%77,%78,%79,%80,%81,%82,%83,%84,%85,%86,%87,%88,%89,%90,%91,%92,%93,%94,%95},"
                 "%96,%97,p,1,1,0,1;}"
                 : "+f"(d[0]), "+f"(d[1]), "+f"(d[2]), "+f"(d[3]), "+f"(d[4]), "+f"(d[5]), "+f"(d[6]), "+f"(d[7]),
                   "+f"(d[8]), "+f"(d[9]), "+f"(d[10]), "+f"(d[11]), "+f"(d[12]), "+f"(d[13]), "+f"(d[14]), "+f"(d[15]),
                   "+f"(d[16]), "+f"(d[17]), "+f"(d[18]), "+f"(d[19]), "+f"(d[20]), "+f"(d[21]), "+f"(d[22]), "+f"(d[23]),
                   "+f"(d[24]), "+f"(d[25]), "+f"(d[26]), "+f"(d[27]), "+f"(d[28]), "+f"(d[29]), "+f"(d[30]), "+f"(d[31]),
                   "+f"(d[32]), "+f"(d[33]), "+f"(d[34]), "+f"(d[35]), "+f"(d[36]), "+f"(d[37]), "+f"(d[38]), "+f"(d[39]),
                   "+f"(d[40]), "+f"(d[41]), "+f"(d[42]), "+f"(d[43]), "+f"(d[44]), "+f"(d[45]), "+f"(d[46]), "+f"(d[47]),
                   "+f"(d[48]), "+f"(d[49]), "+f"(d[50]), "+f"(d[51]), "+f"(d[52]), "+f"(d[53]), "+f"(d[54]), "+f"(d[55]),
                   "+f"(d[56]), "+f"(d[57]), "+f"(d[58]), "+f"(d[59]), "+f"(d[60]), "+f"(d[61]), "+f"(d[62]), "+f"(d[63]),
                   "+f"(d[64]), "+f"(d[65]), "+f"(d[66]), "+f"(d[67]), "+f"(d[68]), "+f"(d[69]), "+f"(d[70]), "+f"(d[71]),
                   "+f"(d[72]), "+f"(d[73]), "+f"(d[74]), "+f"(d[75]), "+f"(d[76]), "+f"(d[77]), "+f"(d[78]), "+f"(d[79]),
                   "+f"(d[80]), "+f"(d[81]), "+f"(d[82]), "+f"(d[83]), "+f"(d[84]), "+f"(d[85]), "+f"(d[86]), "+f"(d[87]),
                   "+f"(d[88]), "+f"(d[89]), "+f"(d[90]), "+f"(d[91]), "+f"(d[92]), "+f"(d[93]), "+f"(d[94]), "+f"(d[95])
                 : "l"(da), "l"(db), "r"(scale_d));
}
__device__ __forceinline__ float gelu_tanh(float hx) {
    const float u = hx * fmaf(hx * hx, 8.f * 0.7978845608028654f * 0.044715f, 2.f * 0.7978845608028654f);
    float th;
    asm("tanh.approx.f32 %0,%1;" : "=f"(th) : "f"(u));
    return fmaf(hx, th, hx);
}

__device__ __forceinline__ void bulk_s2g(void* dst, uint32_t src, uint32_t bytes) {
    asm volatile("cp.async.bulk.global.shared::cta.bulk_group [%0],[%1],%2;" ::"l"(dst), "r"(src), "r"(bytes) : "memory");
}

__device__ __forceinline__ void tma2d_store(const CUtensorMap* tm, uint32_t src, int c0, int c1) {
    asm volatile("cp.async.bulk.tensor.2d.global.shared::cta.bulk_group [%0,{%2,%3}],[%1];" ::"l"(tm), "r"(src), "r"(c0), "r"(c1) : "memory");
}
__device__ __forceinline__ float4 lds128f(uint32_t a) {
    float4 v; asm volatile("ld.shared.v4.f32 {%0,%1,%2,%3},[%4];" : "=f"(v.x), "=f"(v.y), "=f"(v.z), "=f"(v.w) : "r"(a) : "memory");
    return v;
}

constexpr int TB_FULL = 0, TB_EMPTY = 32, TB_SFULL = 64, TB_SEMPTY = 72, TB_TQF = 80, TB_TQE = 96, TB_SQF = 128, TB_SQE = 136, TB_DATA = 160;

__device__ __forceinline__ float4 ldsc128f(uint32_t a) {
    float4 v; asm("ld.shared.v4.f32 {%0,%1,%2,%3},[%4];" : "=f"(v.x), "=f"(v.y), "=f"(v.z), "=f"(v.w) : "r"(a)); return v;
}
__device__ __forceinline__ float2 ldsc64f(uint32_t a) { float2 v; asm("ld.shared.v2.f32 {%0,%1},[%2];" : "=f"(v.x), "=f"(v.y) : "r"(a)); return v; }
__device__ __forceinline__ void store_acquire(uint32_t tb, uint32_t seq, int& dead) {
    int n = dead ? (SPIN_LIMIT << 4) : 0;
    while (true) {
        uint32_t c;
        asm volatile("ld.volatile.shared.u32 %0,[%1];" : "=r"(c) : "r"(tb + TB_SEMPTY) : "memory");
        if (c >= seq) break;
        if (++n > (SPIN_LIMIT << 4)) { dead = 1; break; }
    }
}
__device__ __forceinline__ void ln_stats(uint32_t st, int nt, float cnt, float& mean, float& rstd) {
    float m = 0.f, m2 = 0.f;
    for (int i = 0; i < nt; i++) m += lds64f(st + i * 1024).x;
    m *= 1.f / nt;
    for (int i = 0; i < nt; i++) { const float2 v = lds64f(st + i * 1024); m2 += v.y + cnt * (v.x - m) * (v.x - m); }
    mean = m; rstd = rsqrtf(m2 * (1.f / DM) + 1e-5f);
}

template <int NB>
__device__ __forceinline__ void tail_task(uint32_t sb, volatile int* store_task, int task, uint32_t it, uint32_t seq, int tid, int& dead) {
    constexpr int NJ = 8 * NB, BN = 64 * NB;
    const uint32_t tb = sb + T_BAR;
    const int lane = tid & 31, t = lane & 3, lr = (tid >> 5) * 16 + (lane >> 2);
    const uint32_t mrow = ((tid >> 5) * 16 + ((lane >> 3) & 1) * 8 + (lane & 7)) * 128, mchk = lane >> 4, mxor = lane & 7;
    const int type = task & 3, rb = (task >> 2) & 15, nt = (task >> 6) & 127, ks = (task >> 13) & 15;
    const int KS = type == 0 ? ks_w(rb) : (type == 1 ? 1 : ks_f(rb));
    const int tot = type == 0 ? 64 : (type == 1 ? 9 : 72);
    const int kp = kpart(tot, KS);
    const int nk = ks == KS - 1 ? tot - ks * kp : kp;
    float mean0 = 0.f, mean1 = 0.f, rstd0 = 0.f, rstd1 = 0.f;
    float acc[4 * NJ];
#pragma unroll
    for (int i = 0; i < 4 * NJ; i++) acc[i] = 0.f;
    for (int k = 0; k < nk; k++, it++) {
        const int st = it % G_ST;
        mbar_wait(tb + TB_FULL + 8 * st, (it / G_ST) & 1, dead);
        const uint64_t da = mk_desc(sb + st * G_STAGE + (tid >> 7) * 8192, 16, 1024), db = mk_desc(sb + st * G_STAGE + 16384, 8192, 1024);
        wg_fence();
#pragma unroll
        for (int kk = 0; kk < 4; kk++) wgmma_ss(acc, da + kk * 2, db + kk * 128, 1);
        wg_commit();
        if (type == 1 && k == 5) {
            const int np = ntile(0, rb);
            ln_stats(sb + T_AUX0 + lr * 8, np, (float)(DM / np), mean0, rstd0);
            ln_stats(sb + T_AUX0 + lr * 8 + 64, np, (float)(DM / np), mean1, rstd1);
        }
        if (k > 0) {
            wg_wait<1>();
            if (lane == 0) mbar_arrive(tb + TB_EMPTY + 8 * ((it - 1) % G_ST));
        }
    }
    wg_wait<0>();
    if (lane == 0) mbar_arrive(tb + TB_EMPTY + 8 * ((it - 1) % G_ST));
    if (NB == 1 && ks < KS - 1) {
        store_acquire(tb, seq, dead);
#pragma unroll
        for (int j = 0; j < NJ; j++)
            asm volatile("st.shared.v4.f32 [%0],{%1,%2,%3,%4};" ::"r"(sb + T_STG + j * 4096 + tid * 16), "f"(acc[4 * j]), "f"(acc[4 * j + 1]),
                         "f"(acc[4 * j + 2]), "f"(acc[4 * j + 3]) : "memory");
        fence_async();
        if (tid == 0) *store_task = task;
        mbar_arrive(tb + TB_SFULL);
        TLOG_END();
        return;
    }
    if (ks < KS - 1) {
        float4* part = g_part + (size_t)(((type >> 1) * 16 + rb) * 72 + nt * NJ) * 256 + tid;
        if (KS == 2) {
#pragma unroll
            for (int j = 0; j < NJ; j++) __stcg(part + j * 256, make_float4(acc[4 * j], acc[4 * j + 1], acc[4 * j + 2], acc[4 * j + 3]));
        } else {
#pragma unroll
            for (int j = 0; j < NJ; j++)
                asm volatile("red.relaxed.gpu.global.add.v4.f32 [%0],{%1,%2,%3,%4};" ::"l"(part + j * 256), "f"(acc[4 * j]), "f"(acc[4 * j + 1]),
                             "f"(acc[4 * j + 2]), "f"(acc[4 * j + 3]) : "memory");
        }
        store_acquire(tb, seq, dead);
        if (tid == 0) *store_task = task;
        mbar_arrive(tb + TB_SFULL);
        TLOG_END();
        return;
    }
    if (type != 1) {
        constexpr int NE = NB == 3 ? 4 : 2;
#pragma unroll
        for (int e = 0; e < NE; e++, it++) {
            const int st = it % G_ST;
            mbar_wait(tb + TB_FULL + 8 * st, (it / G_ST) & 1, dead);
            const uint32_t a = sb + st * G_STAGE;
            const int r0 = e * 16, r1 = NB == 3 ? (e == 0 ? 16 : (e == 1 ? 24 : 0)) : (e == 0 ? 8 : 0);
#pragma unroll
            for (int j = r0; j < r1; j += 2) {
                uint32_t rr[4];
                ldsm4(rr, a + ((j >> 3) & 1) * 16384 + mrow + ((((j & 7) + mchk) ^ mxor) << 4));
                float* q = &acc[4 * j];
                q[0] += bf_lo(rr[0]); q[1] += bf_hi(rr[0]); q[2] += bf_lo(rr[1]); q[3] += bf_hi(rr[1]);
                q[4] += bf_lo(rr[2]); q[5] += bf_hi(rr[2]); q[6] += bf_lo(rr[3]); q[7] += bf_hi(rr[3]);
            }
            if (e >= 1) {
                const int j0 = NB == 3 ? (e == 1 ? 20 : (e - 2) * 10) : 0, jn = NB == 3 ? (e == 1 ? 4 : 10) : 8;
#pragma unroll
                for (int j = 0; j < jn; j++) {
                    const float4 pv = lds128f(a + (NB == 3 && e == 1 ? 16384 : 0) + j * 4096 + tid * 16);
                    float* q = &acc[4 * (j0 + j)];
                    q[0] += pv.x; q[1] += pv.y; q[2] += pv.z; q[3] += pv.w;
                }
            }
            __syncwarp();
            if (lane == 0) mbar_arrive(tb + TB_EMPTY + 8 * st);
        }
    }
    uint32_t aux = sb + T_AUX0 + 9216;
    asm volatile("" : "+r"(aux)::"memory");
    uint32_t pk[2 * NJ];
    if (type == 2) {
#pragma unroll
        for (int j = 0; j < NJ; j++) {
            const float2 bv = ldsc64f(sb + T_B2 + (nt * BN + j * 8 + 2 * t) * 4);
            pk[2 * j] = pack_bf16(acc[4 * j] + bv.x, acc[4 * j + 1] + bv.y);
            pk[2 * j + 1] = pack_bf16(acc[4 * j + 2] + bv.x, acc[4 * j + 3] + bv.y);
        }
    } else if (type == 0) {
        float sm0 = 0.f, sm1 = 0.f;
#pragma unroll
        for (int j = 0; j < NJ; j++) {
            pk[2 * j] = pack_bf16(acc[4 * j], acc[4 * j + 1]);
            pk[2 * j + 1] = pack_bf16(acc[4 * j + 2], acc[4 * j + 3]);
            sm0 += bf_lo(pk[2 * j]) + bf_hi(pk[2 * j]);
            sm1 += bf_lo(pk[2 * j + 1]) + bf_hi(pk[2 * j + 1]);
        }
        sm0 += __shfl_xor_sync(~0u, sm0, 1); sm1 += __shfl_xor_sync(~0u, sm1, 1);
        sm0 += __shfl_xor_sync(~0u, sm0, 2); sm1 += __shfl_xor_sync(~0u, sm1, 2);
        sm0 *= (1.f / BN); sm1 *= (1.f / BN);
        float q0 = 0.f, q1 = 0.f;
#pragma unroll
        for (int j = 0; j < NJ; j++) {
            float d;
            d = bf_lo(pk[2 * j]) - sm0; q0 += d * d;
            d = bf_hi(pk[2 * j]) - sm0; q0 += d * d;
            d = bf_lo(pk[2 * j + 1]) - sm1; q1 += d * d;
            d = bf_hi(pk[2 * j + 1]) - sm1; q1 += d * d;
        }
        q0 += __shfl_xor_sync(~0u, q0, 1); q1 += __shfl_xor_sync(~0u, q1, 1);
        q0 += __shfl_xor_sync(~0u, q0, 2); q1 += __shfl_xor_sync(~0u, q1, 2);
        if (t == 0) {
            g_stat[(rb * 9 + nt) * 128 + lr] = make_float2(sm0, q0);
            g_stat[(rb * 9 + nt) * 128 + lr + 8] = make_float2(sm1, q1);
        }
    } else {
        rstd0 *= 0.5f; rstd1 *= 0.5f;
#pragma unroll
        for (int j = 0; j < NJ; j++) {
            const float4 c4 = ldsc128f(aux + (j * 8 + 2 * t) * 8);
            pk[2 * j] = pack_bf16(gelu_tanh(fmaf(rstd0, fmaf(-mean0, c4.x, acc[4 * j]), c4.y)), gelu_tanh(fmaf(rstd0, fmaf(-mean0, c4.z, acc[4 * j + 1]), c4.w)));
            pk[2 * j + 1] = pack_bf16(gelu_tanh(fmaf(rstd1, fmaf(-mean1, c4.x, acc[4 * j + 2]), c4.y)), gelu_tanh(fmaf(rstd1, fmaf(-mean1, c4.z, acc[4 * j + 3]), c4.w)));
        }
    }
    store_acquire(tb, seq, dead);
#pragma unroll
    for (int j = 0; j < NJ; j += 2)
        stsm4(sb + T_STG + mrow + (j >> 3) * 16384 + ((((j & 7) + mchk) ^ mxor) << 4), pk[2 * j], pk[2 * j + 1], pk[2 * j + 2], pk[2 * j + 3]);
    fence_async();
    if (tid == 0) *store_task = task;
    mbar_arrive(tb + TB_SFULL);
    TLOG_END();
}

__global__ void __launch_bounds__(384, 1)
k_tail(const __grid_constant__ CUtensorMap tmWo, const __grid_constant__ CUtensorMap tmW1, const __grid_constant__ CUtensorMap tmW2,
       const __grid_constant__ CUtensorMap tmX, const __grid_constant__ CUtensorMap tmOut,
       const __nv_bfloat16* __restrict__ w1, const __nv_bfloat16* __restrict__ b1, const __nv_bfloat16* __restrict__ b2) {
    extern __shared__ uint8_t smem_raw[];
    const uint32_t sb = (smem_u32(smem_raw) + 1023) & ~1023u;
    uint8_t* const smem = smem_raw + (sb - smem_u32(smem_raw));
    const uint32_t tb = sb + T_BAR;
    volatile int* tq = reinterpret_cast<volatile int*>(smem + T_BAR + TB_DATA);
    volatile int* store_task = tq + 8;
    const int lane = threadIdx.x & 31;
    const int warp = __shfl_sync(~0u, threadIdx.x >> 5, 0);
    int dead = 0;
    if (threadIdx.x == 0) {
        for (int i = 0; i < G_ST; i++) { mbar_init(tb + TB_FULL + 8 * i, 1); mbar_init(tb + TB_EMPTY + 8 * i, 8); }
        mbar_init(tb + TB_SQF, 1); mbar_init(tb + TB_SQE, 1); mbar_init(tb + TB_SFULL, 256); sts32(tb + TB_SEMPTY, 0u); *store_task = 0;
        for (int i = 0; i < 2; i++) { mbar_init(tb + TB_TQF + 8 * i, 1); mbar_init(tb + TB_TQE + 8 * i, 8); }
        asm volatile("fence.mbarrier_init.release.cluster;" ::: "memory");
    }
    if (threadIdx.x == 288) {
        asm volatile("prefetch.tensormap [%0];" ::"l"(&tmWo) : "memory");
        asm volatile("prefetch.tensormap [%0];" ::"l"(&tmW1) : "memory");
        asm volatile("prefetch.tensormap [%0];" ::"l"(&tmW2) : "memory");
    }
    __syncthreads();

    if (warp >= 8) {
      asm volatile("setmaxnreg.dec.sync.aligned.u32 40;");
      if (warp == 10) {
        uint32_t ns = 0;
        int idle = 0;
        if (T_START_DELAY && blockIdx.x < 36) {
            const uint32_t t0 = clk32();
            while ((int)(clk32() - t0) < T_START_DELAY) __nanosleep(500);
        }
        while (true) {
            if (idle == 0) {
                int n = 0;
                while (!mbar_try(tb + TB_SQE, (ns & 1) ^ 1)) { if (++n > (SPIN_LIMIT << 4)) { dead = 1; break; } }
                idle = 1;
            }
            int task = -1;
            uint4 f = make_uint4(0, 0, 0, 0), cn = make_uint4(999, 999, 999, 999);
            if (lane < 17) { f = ld_relaxed4(g_flag + lane * 32); if (lane < 16) cn = ld_relaxed4(g_flag + lane * 32 + 4); }
            const uint32_t init_done = __shfl_sync(~0u, f.x, 16), init_claimed = __shfl_sync(~0u, f.y, 16);
            const int lrb = lane & 15, n0 = ntile(0, lrb), n1 = 8 * ntile(1, lrb);
            const bool oW = cn.x < (uint32_t)(n0 * ks_w(lrb)), o1 = cn.y < (uint32_t)n1, o2 = cn.z < (uint32_t)(ntile(2, lrb) * ks_f(lrb));
            const uint32_t m2 = __ballot_sync(~0u, o2 && f.z >= (uint32_t)n1), m1 = __ballot_sync(~0u, o1 && f.y >= (uint32_t)n0),
                           mW = __ballot_sync(~0u, oW && f.x >= 96u);
            const bool open = __any_sync(~0u, oW || o1 || o2);
            int q = -1, rbq = 0;
            if (init_claimed < (uint32_t)NINIT) q = 3;
            else if (init_done >= (uint32_t)NINIT) {
                if (mW) { q = 0; rbq = __ffs(mW) - 1; }
                else if (m1) { q = 1; rbq = __ffs(m1) - 1; }
                else if (m2) { q = 2; rbq = __ffs(m2) - 1; }
            }
            if (q >= 0) {
                if (lane == 0) {
                    const int nq = ntile(q, rbq);
                    const int n = q == 3 ? NINIT : (q == 1 ? 8 * nq : nq * (q == 2 ? ks_f(rbq) : ks_w(rbq)));
                    uint32_t idx;
                    asm volatile("atom.acquire.gpu.global.add.u32 %0,[%1],1;" : "=r"(idx) : "l"(g_flag + (q == 3 ? FL_CINIT : rbq * 32 + FL_CW + q)) : "memory");
                    if ((int)idx < n) {
                        if (q == 3) task = 3 | (idx << 2);
                        else if (q == 1) task = 1 | (rbq << 2) | (idx << 6);
                        else task = q | (rbq << 2) | ((idx % nq) << 6) | ((FINAL_FIRST ? n / nq - 1 - idx / nq : idx / nq) << 13);
                    }
                }
                task = __shfl_sync(~0u, task, 0);
                if (task < 0) continue;
            } else {
                if (!open || dead || ++idle > (1 << 16)) task = -2;
                else { __nanosleep(POLL_NS); continue; }
            }
            if (lane == 0) { tq[4] = task; mbar_arrive(tb + TB_SQF); }
            ns++; idle = 0;
            if (task < 0) break;
        }
      } else if (warp == 8) {
        uint32_t it = 0, seq = 0;
        for (uint32_t ns = 0;; ns++) {
            int task = -2;
            if (lane == 0) {
                int n0 = 0;
                while (!mbar_try(tb + TB_SQF, ns & 1)) { if (++n0 > (SPIN_LIMIT << 4)) { dead = 1; break; } }
                if (!dead) task = tq[4];
                const int type = task & 3, rb = (task >> 2) & 15, nt = (task >> 6) & 127, ks = (task >> 13) & 15;
                for (int rep = 0; rep < 1; rep++, seq++) {
                    const int wq = seq & 1;
                    int n = 0;
                    while (!mbar_try(tb + TB_TQE + 8 * wq, ((seq >> 1) & 1) ^ 1)) { if (++n > (SPIN_LIMIT << 4)) { dead = 1; break; } }
                    tq[2 * wq] = task; tq[2 * wq + 1] = (int)it;
                    mbar_arrive(tb + TB_TQF + 8 * wq);
                }
                if (task >= 0 && type == 3) mbar_arrive(tb + TB_SQE);
                if (task >= 0 && type != 3) {
                    fence_async_g();
                    const int nb = small_t(type, rb) ? 1 : 3;
                    int KS, tot;
                    const uint8_t* A;
                    const CUtensorMap* tm;
                    if (type == 0) { KS = ks_w(rb); tot = 64; A = g_ox + (size_t)rb * 64 * 16384; tm = &tmWo; }
                    else if (type == 1) { KS = 1; tot = 9; A = g_hb + (size_t)rb * 9 * 16384; tm = &tmW1; }
                    else { KS = ks_f(rb); tot = 72; A = g_ff + (size_t)rb * 72 * 16384; tm = &tmW2; }
                    const int kp = kpart(tot, KS), k1 = ks == KS - 1 ? tot : ks * kp + kp;
                    const int k0 = ks * kp;
                    for (int k = k0; k < k1; k++, it++) {
                        const int st = it % G_ST;
                        mbar_wait(tb + TB_EMPTY + 8 * st, ((it / G_ST) & 1) ^ 1, dead);
                        if (k == k1 - SCHED_AHEAD && !(type != 1 && ks == KS - 1)) mbar_arrive(tb + TB_SQE);
                        const uint32_t a = sb + st * G_STAGE, bb = a + 16384, fb = tb + TB_FULL + 8 * st;
                        const bool aux = type == 1 && k == 5;
                        mbar_expect_tx(fb, 16384 + nb * 8192 + (aux ? ntile(0, rb) * 1024 + nb * 512 : 0));
                        bulk_g2s(a, A + (size_t)k * 16384, 16384, fb);
                        for (int i = 0; i < nb; i++) tma2d(bb + i * 8192, tm, (nt * nb + i) * 64, k * 64, fb);
                        if (aux) {
                            const uint32_t ax = sb + T_AUX0;
                            bulk_g2s(ax, g_stat + rb * 9 * 128, ntile(0, rb) * 1024, fb);
                            bulk_g2s(ax + 9216, g_cb + nt * nb * 64, nb * 512, fb);
                        }
                    }
                    if (type != 1 && ks == KS - 1) {
                        const uint8_t* part = reinterpret_cast<const uint8_t*>(g_part + (size_t)(((type >> 1) * 16 + rb) * 72 + nt * nb * 8) * 256);
                        const int ne = nb == 3 ? 4 : 2;
                        for (int e = 0; e < ne; e++, it++) {
                            const int st = it % G_ST;
                            mbar_wait(tb + TB_EMPTY + 8 * st, ((it / G_ST) & 1) ^ 1, dead);
                            const uint32_t a = sb + st * G_STAGE, fb = tb + TB_FULL + 8 * st;
                            mbar_expect_tx(fb, nb == 3 ? (e < 2 ? 32768 : 40960) : (e == 0 ? 16384 : 32768));
                            for (int i = 2 * e; i < nb && i < 2 * e + 2; i++) {
                                if (type == 0) tma2d(a + (i & 1) * 16384, &tmX, (nt * nb + i) * 64, rb * 128, fb);
                                else bulk_g2s(a + (i & 1) * 16384, g_hb + (size_t)(rb * 9 + nt * nb + i) * 16384, 16384, fb);
                            }
                            if (e == 1) {
                                const uint32_t* dn = g_flag + rb * 32 + FL_DONE + (type >> 1) * 9 + nt;
                                int n = 0;
                                while (ld_acquire1(dn) < (uint32_t)(KS - 1)) { if (++n > SPIN_LIMIT) { dead = 1; break; } __nanosleep(20); }
                                fence_async_g();
                                if (nb == 3) bulk_g2s(a + 16384, part + 81920, 16384, fb);
                                else bulk_g2s(a, part, 32768, fb);
                            } else if (e >= 2) bulk_g2s(a, part + (e - 2) * 40960, 40960, fb);
                        }
                        mbar_arrive(tb + TB_SQE);
                    }
                }
            }
            task = __shfl_sync(~0u, task, 0);
            if (task < 0) break;
        }
      } else if (warp == 9) {
        if (lane == 0) {
            uint32_t ph = 0, rel = 0;
            while (true) {
                int n = 0;
                while (!mbar_try(tb + TB_SFULL, ph)) { if (++n > (SPIN_LIMIT << 4)) { dead = 1; break; } }
                if (dead) break;
                const int task = *store_task;
                if (task < 0) break;
                const int type = task & 3, rb = (task >> 2) & 15, nt = (task >> 6) & 127, ks = (task >> 13) & 15;
                const int nb = small_t(type, rb) ? 1 : 3;
                uint32_t* flag = nullptr;
                bool stored = true, fin0 = false;
                if (type == 3) { flag = g_flag + FL_INIT; stored = false; }
                else if (type == 1) { flag = g_flag + rb * 32 + FL_FF; bulk_s2g(g_ff + (size_t)(rb * 72 + nt * nb) * 16384, sb + T_STG, nb * 16384); }
                else if (ks < (type == 0 ? ks_w(rb) : ks_f(rb)) - 1) {
                    flag = g_flag + rb * 32 + FL_DONE + (type >> 1) * 9 + nt;
                    stored = nb == 1;
                    if (stored)
                        asm volatile("cp.reduce.async.bulk.global.shared::cta.bulk_group.add.f32 [%0],[%1],32768;"
                                     ::"l"(g_part + (size_t)(((type >> 1) * 16 + rb) * 72 + nt * 8) * 256), "r"(sb + T_STG) : "memory");
                }
                else if (type == 0) { fin0 = true; flag = g_flag + rb * 32 + FL_H; bulk_s2g(g_hb + (size_t)(rb * 9 + nt * nb) * 16384, sb + T_STG, nb * 16384); }
                else for (int i = 0; i < nb; i++) tma2d_store(&tmOut, sb + T_STG + i * 16384, (nt * nb + i) * 64, rb * 128);
                if (stored) {
                    asm volatile("cp.async.bulk.commit_group;\ncp.async.bulk.wait_group.read 0;" ::: "memory");
                    asm volatile("st.volatile.shared.u32 [%0],%1;" ::"r"(tb + TB_SEMPTY), "r"(++rel) : "memory");
                    if (fin0) asm volatile("fence.acq_rel.gpu;" ::: "memory");
                    asm volatile("cp.async.bulk.wait_group 0;" ::: "memory");
                    fence_async_g();
                    if (flag) red_add1(flag);
                } else {
                    asm volatile("st.volatile.shared.u32 [%0],%1;" ::"r"(tb + TB_SEMPTY), "r"(++rel) : "memory");
                    asm volatile("red.release.gpu.global.add.u32 [%0],1;" ::"l"(flag) : "memory");
                }
                ph ^= 1;
            }
            pdl_wait();
            if (atomicAdd(g_flag + FL_EXIT, 1u) == gridDim.x - 1) {
                for (int i = 0; i < 17 * 8; i++) reinterpret_cast<uint4*>(g_flag)[i] = make_uint4(0, 0, 0, 0);
            }
        }
      }
    } else {
        asm volatile("setmaxnreg.inc.sync.aligned.u32 232;");
        const int tid = threadIdx.x;
        for (int i = tid; i < DM; i += 256) reinterpret_cast<float*>(smem + T_B2)[i] = __bfloat162float(b2[i]);
        bar_sync(1, 256);
        for (uint32_t seq = 0;; seq++) {
            const int wq = seq & 1;
            {
                int m = 0;
                while (!mbar_try(tb + TB_TQF + 8 * wq, (seq >> 1) & 1)) { if (++m > (SPIN_LIMIT << 4)) { dead = 1; break; } }
            }
            const int task = dead ? -1 : tq[2 * wq];
            const uint32_t it = (uint32_t)tq[2 * wq + 1];
            __syncwarp();
            if (lane == 0) mbar_arrive(tb + TB_TQE + 8 * wq);
            if (task < 0) {
                store_acquire(tb, seq, dead);
                if (tid == 0) *store_task = -1;
                mbar_arrive(tb + TB_SFULL);
                break;
            }
            if ((task & 3) == 3) {
                const int idx = task >> 2;
                store_acquire(tb, seq, dead);
                float a8[8] = {0.f, 0.f, 0.f, 0.f, 0.f, 0.f, 0.f, 0.f};
                const uint4* src = reinterpret_cast<const uint4*>(w1 + idx * 128 + (tid & 15) * 8);
#pragma unroll 12
                for (int k = tid >> 4; k < DM; k += 16) {
                    const uint4 v = src[(size_t)k * (FF / 8)];
                    const uint32_t wv[4] = {v.x, v.y, v.z, v.w};
#pragma unroll
                    for (int j = 0; j < 4; j++) { a8[2 * j] += bf_lo(wv[j]); a8[2 * j + 1] += bf_hi(wv[j]); }
                }
                float* red = reinterpret_cast<float*>(smem + T_STG);
#pragma unroll
                for (int j = 0; j < 8; j++) red[(tid >> 4) * 128 + (tid & 15) * 8 + j] = a8[j];
                bar_sync(1, 256);
                if (tid < 128) {
                    float sum = 0.f;
#pragma unroll
                    for (int j = 0; j < 16; j++) sum += red[j * 128 + tid];
                    g_cb[idx * 128 + tid] = make_float2(sum, 0.5f * __bfloat162float(b1[idx * 128 + tid]));
                }
                for (int u = idx; u < 96; u += NINIT) {
                    const int rbu = (u / 3) & 15;
                    if ((u < 48 ? ks_w(rbu) : ks_f(rbu)) > 2)
                        for (int j = 0; j < 24; j++) g_part[((size_t)u * 24 + j) * 256 + tid] = make_float4(0.f, 0.f, 0.f, 0.f);
                }
                if (tid == 0) *store_task = task;
                mbar_arrive(tb + TB_SFULL);
                TLOG_END();
            } else if (small_t(task & 3, (task >> 2) & 15)) tail_task<1>(sb, store_task, task, it, seq, tid, dead);
            else tail_task<3>(sb, store_task, task, it, seq, tid, dead);
        }
    }
}

typedef CUresult (*EncodeFn)(CUtensorMap*, CUtensorMapDataType, cuuint32_t, void*, const cuuint64_t*, const cuuint64_t*,
                             const cuuint32_t*, const cuuint32_t*, CUtensorMapInterleave, CUtensorMapSwizzle,
                             CUtensorMapL2promotion, CUtensorMapFloatOOBfill);

void make_map(EncodeFn enc, CUtensorMap* tm, const void* ptr, uint64_t inner, uint64_t outer, uint32_t box_inner, uint32_t box_outer) {
    cuuint64_t dims[2] = {inner, outer};
    cuuint64_t strides[1] = {inner * 2};
    cuuint32_t box[2] = {box_inner, box_outer};
    cuuint32_t es[2] = {1, 1};
    enc(tm, CU_TENSOR_MAP_DATA_TYPE_BFLOAT16, 2, const_cast<void*>(ptr), dims, strides, box, es, CU_TENSOR_MAP_INTERLEAVE_NONE,
        CU_TENSOR_MAP_SWIZZLE_128B, CU_TENSOR_MAP_L2_PROMOTION_L2_256B, CU_TENSOR_MAP_FLOAT_OOB_FILL_NONE);
}

}

extern "C" void kernel_launch(void* const* d_in, const int* in_sizes, int n_in, void* d_out, int out_size) {
    const __nv_bfloat16* x = (const __nv_bfloat16*)d_in[0];
    const __nv_bfloat16* mem0 = (const __nv_bfloat16*)d_in[1];
    const __nv_bfloat16* Wq = (const __nv_bfloat16*)d_in[2];
    const __nv_bfloat16* Wk = (const __nv_bfloat16*)d_in[3];
    const __nv_bfloat16* Wv = (const __nv_bfloat16*)d_in[4];
    const __nv_bfloat16* Wo = (const __nv_bfloat16*)d_in[5];
    const __nv_bfloat16* w1 = (const __nv_bfloat16*)d_in[8];
    const __nv_bfloat16* b1 = (const __nv_bfloat16*)d_in[9];
    const __nv_bfloat16* w2 = (const __nv_bfloat16*)d_in[10];
    const __nv_bfloat16* b2 = (const __nv_bfloat16*)d_in[11];
    __nv_bfloat16* out = (__nv_bfloat16*)d_out;
    cudaStream_t stream = cudaStreamPerThread;

    static EncodeFn enc = nullptr;
    if (!enc) {
        cudaDriverEntryPointQueryResult qr;
        void* fn = nullptr;
        cudaGetDriverEntryPoint("cuTensorMapEncodeTiled", &fn, cudaEnableDefault, &qr);
        enc = (EncodeFn)fn;
        cudaFuncSetAttribute(k_chain, cudaFuncAttributeMaxDynamicSharedMemorySize, SM_CHAIN_BYTES);
        cudaFuncSetAttribute(k_tail, cudaFuncAttributeMaxDynamicSharedMemorySize, T_SMEM);
    }
    CUtensorMap tWq, tWk, tWv, tWo, tW1, tW2, tX, tOut;
    make_map(enc, &tWq, Wq, HD, DM, 64, 192);
    make_map(enc, &tWk, Wk, HD, DM, 64, 192);
    make_map(enc, &tWv, Wv, HD, DM, 64, 192);
    make_map(enc, &tX, x, DM, SEQ, 64, 128);
    make_map(enc, &tOut, out, DM, SEQ, 64, 128);
    make_map(enc, &tWo, Wo, DM, HD, 64, 64);
    make_map(enc, &tW1, w1, FF, DM, 64, 64);
    make_map(enc, &tW2, w2, DM, FF, 64, 64);

    {
        cudaLaunchConfig_t cfg = {};
        cfg.gridDim = dim3(96); cfg.blockDim = dim3(384); cfg.dynamicSmemBytes = SM_CHAIN_BYTES; cfg.stream = stream;
        void* px;
        cudaGetSymbolAddress(&px, g_xch);
        uint8_t* xb = reinterpret_cast<uint8_t*>((reinterpret_cast<uintptr_t>(px) + 65535) & ~(uintptr_t)65535);
        cudaLaunchKernelEx(&cfg, k_chain, tWq, tWk, tWv, tWo, x, mem0, xb);
    }
    {
        cudaLaunchConfig_t cfg = {};
        cfg.gridDim = dim3(132); cfg.blockDim = dim3(384); cfg.dynamicSmemBytes = T_SMEM; cfg.stream = stream;
        cudaLaunchAttribute at[1];
        at[0].id = cudaLaunchAttributeProgrammaticStreamSerialization;
        at[0].val.programmaticStreamSerializationAllowed = 1;
        cfg.attrs = at; cfg.numAttrs = 1;
        cudaLaunchKernelEx(&cfg, k_tail, tWo, tW1, tW2, tX, tOut, w1, b1, b2);
    }
}
```
